```python
import torch

def _softmax(x, axis=-1):
    return torch.softmax(x, dim=axis)
def _gelu(x):
    return torch.nn.functional.gelu(x, approximate="tanh")
def _silu(x):
    return torch.nn.functional.silu(x)
def _sigmoid(x):
    return torch.sigmoid(x)
def _layernorm(x, axis=-1, eps=1e-5):
    m = x.mean(dim=axis, keepdim=True)
    v = x.var(dim=axis, keepdim=True, unbiased=False)
    return (x - m) / torch.sqrt(v + eps)
def _scatter_add(tgt, idx, src, axis=0):
    return tgt.clone().index_add_(axis, idx, src)
def _segment_sum(src, seg, n):
    out = torch.zeros((n,) + src.shape[1:], dtype=src.dtype)
    return out.index_add_(0, seg, src)
def _pad(x, pw):
    flat = tuple(v for pair in reversed(pw) for v in pair)
    return torch.nn.functional.pad(x, flat)

kernel_name = 'parallel_sum__mha_block_cached__mixer_token_mlp__decode'

def setup_inputs():

    _w = (lambda a: (lambda t: t.to(torch.bfloat16) if t.is_floating_point() else t)(torch.as_tensor(a)))
    def _A_setup():
        B, Sq, D = 1, 1, 640
        H, Sk, Dh = 32, 32768, 128
        return {
            "x": _w((lambda *s: torch.randn(*s, dtype=torch.bfloat16) * 0.05)(B, Sq, D)),
            "k_cache": _w((lambda *s: torch.randn(*s, dtype=torch.bfloat16) * 3.2)(B, H, Sk, Dh)),
            "v_cache": _w((lambda *s: torch.randn(*s, dtype=torch.bfloat16) * 0.8)(B, H, Sk, Dh)),
            "wq": _w((lambda *s: torch.randn(*s, dtype=torch.bfloat16) * 3.2)(D, H * Dh) * (D ** -0.5)),
            "wo": _w((lambda *s: torch.randn(*s, dtype=torch.bfloat16) * 0.8)(H * Dh, D) * ((H * Dh) ** -0.5)),
        }
    _A_in = _A_setup()

    def _B_setup():
        B, S, D, F = 1, 1, 640, 1728
        return {
            "x": _w((lambda *s: torch.randn(*s, dtype=torch.bfloat16) * 0.05)(B, S, D)),
            "w1": _w((lambda *s: torch.randn(*s, dtype=torch.bfloat16) * 0.8)(S, F) * (S ** -0.5)),
            "b1": _w((lambda *s: torch.randn(*s, dtype=torch.bfloat16) * 0.8)(F) * 0.02),
            "w2": _w((lambda *s: torch.randn(*s, dtype=torch.bfloat16) * 0.8)(F, S) * (F ** -0.5)),
            "b2": _w((lambda *s: torch.randn(*s, dtype=torch.bfloat16) * 0.8)(S) * 0.02),
        }
    _B_in = _B_setup()

    return {
        "A_x": _A_in["x"],
        "A_k_cache": _A_in["k_cache"],
        "A_v_cache": _A_in["v_cache"],
        "A_wq": _A_in["wq"],
        "A_wo": _A_in["wo"],
        "B_x": _B_in["x"],
        "B_w1": _B_in["w1"],
        "B_b1": _B_in["b1"],
        "B_w2": _B_in["w2"],
        "B_b2": _B_in["b2"],
    }

def reference(A_x, A_k_cache, A_v_cache, A_wq, A_wo, B_x, B_w1, B_b1, B_w2, B_b2):
    def _A_ref(x, k_cache, v_cache, wq, wo):
        B, Sq, D = x.shape
        H, Dh = 32, 128
        q = (lambda x, *d: x.permute(*d))((x @ wq).reshape(B, Sq, H, Dh), 0, 2, 1, 3)
        scores = torch.einsum("bhqd,bhkd->bhqk", q, k_cache) * (Dh ** -0.5)
        p = _softmax(scores, axis=-1)
        o = torch.einsum("bhqk,bhkd->bhqd", p, v_cache)
        return (lambda x, *d: x.permute(*d))(o, 0, 2, 1, 3).reshape(B, Sq, H * Dh) @ wo

    def _B_ref(x, w1, b1, w2, b2):
        B, S, D = x.shape
        h = _layernorm(x, axis=-1)
        u = torch.einsum("bsd,sf->bdf", h, w1) + b1
        u = _gelu(u)
        y = torch.einsum("bdf,fs->bds", u, w2) + b2
        return (lambda x, *d: x.permute(*d))(y, 0, 2, 1)

    x = A_x
    xn = _layernorm(x, axis=-1)
    return x + _A_ref(xn, A_k_cache, A_v_cache, A_wq, A_wo) + _B_ref(xn, B_w1, B_b1, B_w2, B_b2)
```

```cpp
#include <cuda_runtime.h>
#include <cuda.h>
#include <cuda_bf16.h>
#include <stdint.h>

namespace {

constexpr int D_MODEL = 640;
constexpr int NH = 32;
constexpr int SK = 32768;
constexpr int DH = 128;
constexpr int FF = 1728;

constexpr int SPLITS = 4;
constexpr int NCTA = NH * SPLITS;
constexpr int KEYS_PER_CTA = SK / SPLITS;
constexpr int TILE_KEYS = 64;
constexpr int SLOT_BYTES = TILE_KEYS * DH * 2;
constexpr int NTILES = KEYS_PER_CTA / TILE_KEYS;
constexpr int NITEMS = 2 * NTILES;
constexpr int NSLOT = 12;

#define FILL_W 3
constexpr int FILL_WINDOW = FILL_W;

constexpr int QROWS = D_MODEL / SPLITS;
constexpr int WO_ROWS = DH / SPLITS;
constexpr int WO_ROW_BYTES = D_MODEL * 2;
constexpr int WO_PITCH = WO_ROW_BYTES + 16;
constexpr int NFIN = D_MODEL / 8;

constexpr int NCW = 8;
constexpr int NTHREADS = 32 * (NCW + 2);

constexpr int SM_RING = 0;
constexpr int WO_SLOT = NITEMS % NSLOT;
constexpr int SM_WBUF = WO_SLOT * SLOT_BYTES;
constexpr int WQ_SLOT = NSLOT - 3;
constexpr int SM_WQ = WQ_SLOT * SLOT_BYTES;
constexpr int SM_RED = NSLOT * SLOT_BYTES;
constexpr int SM_ML = SM_RED + NCW * DH * 4;
constexpr int SM_QS = SM_ML + NCW * 8;
constexpr int SM_OB = SM_QS + DH * 2;
constexpr int SM_FIN = SM_OB + WO_ROWS * 2;
constexpr int SM_MLP = SM_FIN + NCW * 8 * 4;
constexpr int SM_MW = SM_MLP + 8 * 4;
constexpr int SM_BAR = SM_MW + 3 * FF * 2;
constexpr int SM_TOTAL = SM_BAR + (2 * NSLOT + 4) * 8;
static_assert(SM_MW % 16 == 0 && SM_BAR % 8 == 0, "alignment");

static_assert(NSLOT % 4 == 0 && WO_SLOT + 3 <= NSLOT && WO_ROWS * WO_PITCH <= 3 * SLOT_BYTES, "ring layout");

constexpr float LOG2E = 1.4426950408889634f;
constexpr float SM_SCALE = 0.08838834764831845f;
constexpr float LN_EPS = 1e-5f;
constexpr uint32_t SPIN_LIMIT = 1u << 24;

struct Scratch {
    unsigned long long qx[NH][SPLITS][DH];
    unsigned long long ox[NH][SPLITS][DH + 8];
    unsigned long long tx[NFIN][NCTA][8];
    unsigned int epoch;
};
__device__ __align__(128) Scratch g_scr;

#define TL(i) do { } while (0)
#define TW(i) do { } while (0)
#define TL0() do { } while (0)
#define TLMID() do { } while (0)
#define TLEND() do { } while (0)

__device__ __forceinline__ uint32_t smem_u32(const void* p) { return (uint32_t)__cvta_generic_to_shared(p); }

__device__ __forceinline__ void mbar_init(uint32_t bar, uint32_t cnt) {
    asm volatile("mbarrier.init.shared::cta.b64 [%0], %1;" ::"r"(bar), "r"(cnt) : "memory");
}
__device__ __forceinline__ void mbar_expect_tx(uint32_t bar, uint32_t bytes) {
    asm volatile("mbarrier.arrive.expect_tx.shared::cta.b64 _, [%0], %1;" ::"r"(bar), "r"(bytes) : "memory");
}
__device__ __forceinline__ void mbar_arrive(uint32_t bar) {
    asm volatile("mbarrier.arrive.shared::cta.b64 _, [%0];" ::"r"(bar) : "memory");
}
__device__ __forceinline__ void mbar_wait(uint32_t bar, uint32_t parity) {
    uint32_t done, it = 0;
    do {
        asm volatile(
            "{\n.reg .pred p;\n"
            "mbarrier.try_wait.parity.shared::cta.b64 p, [%1], %2;\n"
            "selp.u32 %0, 1, 0, p;\n}"
            : "=r"(done) : "r"(bar), "r"(parity) : "memory");
        if (++it > SPIN_LIMIT) __trap();
    } while (!done);
}
__device__ __forceinline__ void bulk_load(uint32_t dst, const void* src, uint32_t bytes, uint32_t bar) {
    asm volatile("cp.async.bulk.shared::cluster.global.mbarrier::complete_tx::bytes [%0], [%1], %2, [%3];"
                 ::"r"(dst), "l"(src), "r"(bytes), "r"(bar) : "memory");
}
__device__ __forceinline__ void bulk_load_stream(uint32_t dst, const void* src, uint32_t bytes, uint32_t bar, uint64_t pol) {
    asm volatile("cp.async.bulk.shared::cluster.global.mbarrier::complete_tx::bytes.L2::cache_hint [%0], [%1], %2, [%3], %4;"
                 ::"r"(dst), "l"(src), "r"(bytes), "r"(bar), "l"(pol) : "memory");
}
__device__ __forceinline__ void ldsm_x4(uint32_t (&r)[4], uint32_t addr) {
    asm volatile("ldmatrix.sync.aligned.m8n8.x4.shared.b16 {%0,%1,%2,%3}, [%4];"
                 : "=r"(r[0]), "=r"(r[1]), "=r"(r[2]), "=r"(r[3]) : "r"(addr) : "memory");
}
__device__ __forceinline__ void ldsm_x4_t(uint32_t (&r)[4], uint32_t addr) {
    asm volatile("ldmatrix.sync.aligned.m8n8.x4.trans.shared.b16 {%0,%1,%2,%3}, [%4];"
                 : "=r"(r[0]), "=r"(r[1]), "=r"(r[2]), "=r"(r[3]) : "r"(addr) : "memory");
}
__device__ __forceinline__ void mma_bf16(float (&d)[4], uint32_t a0, uint32_t a1, uint32_t a2, uint32_t a3,
                                         uint32_t b0, uint32_t b1) {
    asm volatile("mma.sync.aligned.m16n8k16.row.col.f32.bf16.bf16.f32 {%0,%1,%2,%3}, {%4,%5,%6,%7}, {%8,%9}, {%0,%1,%2,%3};"
                 : "+f"(d[0]), "+f"(d[1]), "+f"(d[2]), "+f"(d[3])
                 : "r"(a0), "r"(a1), "r"(a2), "r"(a3), "r"(b0), "r"(b1));
}
__device__ __forceinline__ float ex2(float x) {
    float y;
    asm("ex2.approx.ftz.f32 %0, %1;" : "=f"(y) : "f"(x));
    return y;
}
__device__ __forceinline__ float bf16r(float x) { return __bfloat162float(__float2bfloat16_rn(x)); }
__device__ __forceinline__ float bf_lo(uint32_t u) { return __uint_as_float(u << 16); }
__device__ __forceinline__ float bf_hi(uint32_t u) { return __uint_as_float(u & 0xffff0000u); }
__device__ __forceinline__ uint32_t pack_bf16(float lo, float hi) {
    uint32_t r;
    asm("cvt.rn.bf16x2.f32 %0, %1, %2;" : "=r"(r) : "f"(hi), "f"(lo));
    return r;
}
__device__ __forceinline__ void named_sync(int id, int n) { asm volatile("bar.sync %0, %1;" ::"r"(id), "r"(n) : "memory"); }
__device__ __forceinline__ void named_arrive(int id, int n) { asm volatile("bar.arrive %0, %1;" ::"r"(id), "r"(n) : "memory"); }

__device__ __forceinline__ void ll_store(unsigned long long* p, float v, uint32_t tag) {
    unsigned long long w = ((unsigned long long)tag << 32) | (unsigned long long)__float_as_uint(v);
    asm volatile("st.relaxed.gpu.global.b64 [%0], %1;" ::"l"(p), "l"(w) : "memory");
}
__device__ __forceinline__ unsigned long long ll_load(const unsigned long long* p) {
    unsigned long long w;
    asm volatile("ld.relaxed.gpu.global.b64 %0, [%1];" : "=l"(w) : "l"(p) : "memory");
    return w;
}
__device__ __forceinline__ void ll_load2(const unsigned long long* p, unsigned long long& a, unsigned long long& b) {
    asm volatile("ld.relaxed.gpu.global.v2.b64 {%0,%1}, [%2];" : "=l"(a), "=l"(b) : "l"(p) : "memory");
}
__device__ __forceinline__ bool ll_ok(unsigned long long w, uint32_t tag) { return (uint32_t)(w >> 32) == tag; }
__device__ __forceinline__ float ll_val(unsigned long long w) { return __uint_as_float((uint32_t)w); }

__device__ __forceinline__ uint4 ldg_stream(const void* p) {
    uint4 v;
    asm volatile("ld.global.nc.L1::no_allocate.v4.u32 {%0,%1,%2,%3}, [%4];"
                 : "=r"(v.x), "=r"(v.y), "=r"(v.z), "=r"(v.w) : "l"(p));
    return v;
}
__device__ __forceinline__ float warp_sum(float v) {
#pragma unroll
    for (int o = 16; o > 0; o >>= 1) v += __shfl_xor_sync(0xffffffffu, v, o);
    return v;
}
__device__ __forceinline__ float warp_max(float v) {
#pragma unroll
    for (int o = 16; o > 0; o >>= 1) v = fmaxf(v, __shfl_xor_sync(0xffffffffu, v, o));
    return v;
}

__device__ __forceinline__ void ln_stats(const float (&v)[20], float& mean_b, float& den_b) {
    float s = 0.f;
#pragma unroll
    for (int i = 0; i < 20; i++) s += v[i];
    const float mean = warp_sum(s) * (1.0f / D_MODEL);
    float q = 0.f;
#pragma unroll
    for (int i = 0; i < 20; i++) { const float d = v[i] - mean; q = fmaf(d, d, q); }
    const float var = warp_sum(q) * (1.0f / D_MODEL);
    mean_b = bf16r(mean);
    den_b = bf16r(sqrtf(bf16r(bf16r(var) + LN_EPS)));
}
__device__ __forceinline__ float ln_apply(float x, float mean_b, float den_b) {
    return bf16r(__fdiv_rn(bf16r(x - mean_b), den_b));
}
__device__ __forceinline__ uint2 ldg_u64(const void* p) {
    uint2 v;
    asm volatile("ld.global.nc.v2.u32 {%0,%1}, [%2];" : "=r"(v.x), "=r"(v.y) : "l"(p));
    return v;
}
__device__ __forceinline__ uint32_t ldg_u16(const void* p) {
    uint16_t v;
    asm volatile("ld.global.nc.u16 %0, [%1];" : "=h"(v) : "l"(p));
    return v;
}
__device__ __forceinline__ void unpack_x20(const uint2 (&u)[5], float (&v)[20]) {
#pragma unroll
    for (int i = 0; i < 5; i++) {
        v[4 * i + 0] = bf_lo(u[i].x); v[4 * i + 1] = bf_hi(u[i].x);
        v[4 * i + 2] = bf_lo(u[i].y); v[4 * i + 3] = bf_hi(u[i].y);
    }
}

__global__ void __launch_bounds__(NTHREADS, 1)
fused_decode_kernel(const __grid_constant__ CUtensorMap tm_wq,
                    const __nv_bfloat16* __restrict__ x, const __nv_bfloat16* __restrict__ kc,
                    const __nv_bfloat16* __restrict__ vc, const __nv_bfloat16* __restrict__ wo, const __nv_bfloat16* __restrict__ w1,
                    const __nv_bfloat16* __restrict__ b1, const __nv_bfloat16* __restrict__ w2,
                    const __nv_bfloat16* __restrict__ b2, __nv_bfloat16* __restrict__ out)
{
    extern __shared__ __align__(1024) uint8_t smem[];
    const uint32_t sbase = smem_u32(smem);
    const int tid = threadIdx.x, warp = tid >> 5, lane = tid & 31;
    const int cta = blockIdx.x, head = cta / SPLITS, split = cta % SPLITS;
    const uint32_t bar_full = sbase + SM_BAR, bar_empty = bar_full + NSLOT * 8, bar_w = bar_empty + NSLOT * 8, bar_m = bar_w + 8,
                   bar_q = bar_m + 8, bar_qd = bar_q + 8;

    const uint8_t* kbase = reinterpret_cast<const uint8_t*>(kc) + ((size_t)head * SK + (size_t)split * KEYS_PER_CTA) * (DH * 2);
    const uint8_t* vbase = reinterpret_cast<const uint8_t*>(vc) + ((size_t)head * SK + (size_t)split * KEYS_PER_CTA) * (DH * 2);

    if (tid == 32) TL0();
    uint2 xraw[5];
    uint32_t xrow[10];
    uint32_t epoch = 0, xfin = 0;
    if (warp == 0) {
        if (lane == 0) {
            asm volatile("prefetch.tensormap [%0];" ::"l"(&tm_wq) : "memory");
            mbar_init(bar_q, 1);
            mbar_init(bar_qd, NCW);
            for (int s = 0; s < NSLOT; s++) {
                mbar_init(bar_full + s * 8, 1);
                mbar_init(bar_empty + s * 8, NCW / 2);
            }
            mbar_init(bar_w, 1);
            mbar_init(bar_m, 1);
            asm volatile("fence.mbarrier_init.release.cluster;" ::: "memory");
            asm volatile("fence.proxy.async.shared::cta;" ::: "memory");
            mbar_expect_tx(bar_q, QROWS * DH * 2);
            asm volatile("cp.async.bulk.tensor.2d.shared::cluster.global.mbarrier::complete_tx::bytes [%0], [%1, {%3, %4}], [%2];"
                         ::"r"(sbase + SM_WQ), "l"(&tm_wq), "r"(bar_q), "r"(head * DH), "r"(split * QROWS) : "memory");
            TL(18);
        }
    } else {
        if (warp <= NCW) {
            const int ct = tid - 32;
            asm volatile("ld.volatile.global.u32 %0, [%1];" : "=r"(epoch) : "l"(&g_scr.epoch) : "memory");
#pragma unroll
            for (int i = 0; i < 10; i++) xrow[i] = ldg_u16(x + split * QROWS + (ct >> 4) + 16 * i);
            xfin = ldg_u16(x + (cta < NFIN ? cta * 8 : 0) + (ct & 7));
        }
#pragma unroll
        for (int i = 0; i < 5; i++) xraw[i] = ldg_u64(reinterpret_cast<const uint2*>(x) + lane + 32 * i);
        if (tid == 32) TL(16);
        if (warp <= NCW) {
            const int ct = tid - 32;
            if (ct < DH) ll_store(&g_scr.qx[head][split][ct], 0.f, 0u);
            if (ct < DH + 8) ll_store(&g_scr.ox[head][split][ct], 0.f, 0u);
#pragma unroll
            for (int k = 0; k < 3; k++) {
                const int idx = ct + 256 * k;
                if (idx < D_MODEL) ll_store(&g_scr.tx[idx >> 3][cta][idx & 7], 0.f, 0u);
            }
        }
    }
    if (tid == 32) TL(17);
    __syncthreads();

    if (warp == 0) {
        if (lane == 0) {
            TL(15);
            uint64_t pol;
            asm volatile("createpolicy.fractional.L2::evict_first.b64 %0, 1.0;" : "=l"(pol));
            for (int i = 0; i < NSLOT; i++) {
                if (i >= FILL_WINDOW) mbar_wait(bar_full + (i - FILL_WINDOW) * 8, 0);
                if (i == WQ_SLOT) mbar_wait(bar_qd, 0);
                mbar_expect_tx(bar_full + i * 8, SLOT_BYTES);
                bulk_load_stream(sbase + SM_RING + i * SLOT_BYTES, ((i & 1) ? vbase : kbase) + (size_t)(i >> 1) * SLOT_BYTES,
                                 SLOT_BYTES, bar_full + i * 8, pol);
            }
            if (cta < NFIN) {
                mbar_expect_tx(bar_m, 3 * FF * 2);
                bulk_load(sbase + SM_MW, w1, FF * 2, bar_m);
                bulk_load(sbase + SM_MW + FF * 2, b1, FF * 2, bar_m);
                bulk_load(sbase + SM_MW + 2 * FF * 2, w2, FF * 2, bar_m);
            }
            int slot = 0;
            uint32_t ph = 0;
            for (int i = NSLOT; i < NITEMS; i++) {
                mbar_wait(bar_empty + slot * 8, ph);
                mbar_expect_tx(bar_full + slot * 8, SLOT_BYTES);
                bulk_load_stream(sbase + SM_RING + slot * SLOT_BYTES, ((i & 1) ? vbase : kbase) + (size_t)(i >> 1) * SLOT_BYTES,
                                 SLOT_BYTES, bar_full + slot * 8, pol);
                if (++slot == NSLOT) { slot = 0; ph ^= 1; }
            }
            TL(11);
            for (int k = 0; k < 3; k++) {
                mbar_wait(bar_empty + slot * 8, ph);
                if (++slot == NSLOT) { slot = 0; ph ^= 1; }
            }
            mbar_expect_tx(bar_w, WO_ROWS * WO_ROW_BYTES);
        }
        __syncwarp();
        bulk_load(sbase + SM_WBUF + lane * WO_PITCH,
                  wo + (size_t)(head * DH + split * WO_ROWS + lane) * D_MODEL, WO_ROW_BYTES, bar_w);
    } else if (warp <= NCW) {
        const int cw = warp - 1, ct = tid - 32;
        const int g = lane >> 2, t = lane & 3;
        float* red = reinterpret_cast<float*>(smem + SM_RED);
        const uint32_t tag = epoch + 1u;

        {
            float xv[20];
            unpack_x20(xraw, xv);
            float mean_b, den_b;
            ln_stats(xv, mean_b, den_b);
            if (ct == 0) TL(12);
            float a[8];
#pragma unroll
            for (int j = 0; j < 8; j++) a[j] = 0.f;
            float xn[10];
#pragma unroll
            for (int i = 0; i < 10; i++) xn[i] = ln_apply(bf_lo(xrow[i]), mean_b, den_b);
            mbar_wait(bar_q, 0);
            if (ct == 0) TL(19);
            const uint4* wsm = reinterpret_cast<const uint4*>(smem + SM_WQ) + ct;
#pragma unroll
            for (int i = 0; i < 10; i++) {
                const uint4 w = wsm[i * 256];
                a[0] = fmaf(xn[i], bf_lo(w.x), a[0]); a[1] = fmaf(xn[i], bf_hi(w.x), a[1]);
                a[2] = fmaf(xn[i], bf_lo(w.y), a[2]); a[3] = fmaf(xn[i], bf_hi(w.y), a[3]);
                a[4] = fmaf(xn[i], bf_lo(w.z), a[4]); a[5] = fmaf(xn[i], bf_hi(w.z), a[5]);
                a[6] = fmaf(xn[i], bf_lo(w.w), a[6]); a[7] = fmaf(xn[i], bf_hi(w.w), a[7]);
            }
            __syncwarp();
            if (lane == 0) mbar_arrive(bar_qd);
#pragma unroll
            for (int j = 0; j < 8; j++) a[j] += __shfl_xor_sync(0xffffffffu, a[j], 16);
            if (lane < 16) {
                float4* dst = reinterpret_cast<float4*>(red + cw * DH + lane * 8);
                dst[0] = make_float4(a[0], a[1], a[2], a[3]);
                dst[1] = make_float4(a[4], a[5], a[6], a[7]);
            }
            named_sync(1, NCW * 32);
            if (ct == 0) TL(1);
            if (ct < DH) {
                float s = 0.f;
#pragma unroll
                for (int w = 0; w < NCW; w++) s += red[w * DH + ct];
                ll_store(&g_scr.qx[head][split][ct], s, tag);
                unsigned long long w4[SPLITS];
                uint32_t it = 0;
                bool ok;
                do {
#pragma unroll
                    for (int i = 0; i < SPLITS; i++) w4[i] = ll_load(&g_scr.qx[head][i][ct]);
                    ok = true;
#pragma unroll
                    for (int i = 0; i < SPLITS; i++) ok = ok && ll_ok(w4[i], tag);
                    if (++it > SPIN_LIMIT) __trap();
                } while (!ok);
                const float q = (ll_val(w4[0]) + ll_val(w4[1])) + (ll_val(w4[2]) + ll_val(w4[3]));
                reinterpret_cast<__nv_bfloat16*>(smem + SM_QS)[ct] = __float2bfloat16_rn(q);
            }
            named_sync(1, NCW * 32);
            if (ct == 0) TL(2);
        }

        uint32_t qf[8][2];
#pragma unroll
        for (int s = 0; s < 8; s++) {
            const uint32_t* qs = reinterpret_cast<const uint32_t*>(smem + SM_QS);
            qf[s][0] = qs[4 * (s ^ g) + t];
            qf[s][1] = qs[32 + 4 * (s ^ g) + t];
        }

        float acc[8][4];
#pragma unroll
        for (int c = 0; c < 8; c++) { acc[c][0] = acc[c][1] = acc[c][2] = acc[c][3] = 0.f; }
        float m_run = -INFINITY, l_run = 0.f;
        const bool valid = (t == (g >> 1));
        const bool odd = g & 1;
        const uint32_t sel0 = odd ? 0x1044u : 0x4410u;
        const uint32_t sel1 = odd ? 0x3244u : 0x4432u;
        const int mi = lane >> 3, rho = lane & 7;
        const uint32_t lane_off = (uint32_t)((cw & 3) * 16 + rho + 8 * (mi >> 1)) * 256u + (uint32_t)(mi & 1) * 128u + (uint32_t)rho * 16u;

        int slot = 2 * (cw >> 2);
        uint32_t ph = 0;
        for (int tile = cw >> 2; tile < NTILES; tile += 2) {
            const int slotv = slot + 1;
            const uint32_t ka = sbase + SM_RING + slot * SLOT_BYTES + lane_off;
            const uint32_t va = sbase + SM_RING + slotv * SLOT_BYTES + lane_off;

            mbar_wait(bar_full + slot * 8, ph);
            if (ct == 0 && tile == 0) TL(13);
            if (ct == 0 && tile == 6) TL(14);
            float s0[4] = {0.f, 0.f, 0.f, 0.f}, s1[4] = {0.f, 0.f, 0.f, 0.f};
#pragma unroll
            for (int s = 0; s < 8; s += 2) {
                uint32_t r[4], u[4];
                ldsm_x4(r, ka ^ (uint32_t)(s << 4));
                ldsm_x4(u, ka ^ (uint32_t)((s + 1) << 4));
                mma_bf16(s0, r[0], r[2], r[1], r[3], qf[s][0], qf[s][1]);
                mma_bf16(s1, u[0], u[2], u[1], u[3], qf[s + 1][0], qf[s + 1][1]);
            }
            __syncwarp();
            if (lane == 0) mbar_arrive(bar_empty + slot * 8);

            float sa = odd ? (s0[1] + s1[1]) : (s0[0] + s1[0]);
            float sb = odd ? (s0[3] + s1[3]) : (s0[2] + s1[2]);
            sa = valid ? bf16r(bf16r(sa) * SM_SCALE) : -INFINITY;
            sb = valid ? bf16r(bf16r(sb) * SM_SCALE) : -INFINITY;
            const float smax = fmaxf(sa, sb);
            if (__any_sync(0xffffffffu, smax > m_run)) {
                const float m_new = fmaxf(m_run, warp_max(smax));
                const float sc = ex2((m_run - m_new) * LOG2E);
#pragma unroll
                for (int c = 0; c < 8; c++) { acc[c][0] *= sc; acc[c][1] *= sc; acc[c][2] *= sc; acc[c][3] *= sc; }
                l_run *= sc;
                m_run = m_new;
            }
            const float pa = ex2((sa - m_run) * LOG2E);
            const float pb = ex2((sb - m_run) * LOG2E);
            l_run += pa + pb;
            const uint32_t pk = pack_bf16(pa, pb);
            const uint32_t b0 = __byte_perm(pk, 0u, sel0);
            const uint32_t b1 = __byte_perm(pk, 0u, sel1);

            mbar_wait(bar_full + slotv * 8, ph);
#pragma unroll
            for (int c = 0; c < 8; c++) {
                uint32_t r[4];
                ldsm_x4_t(r, va ^ (uint32_t)(c << 4));
                mma_bf16(acc[c], r[0], r[1], r[2], r[3], b0, b1);
            }
            __syncwarp();
            if (lane == 0) mbar_arrive(bar_empty + slotv * 8);

            slot += 4;
            if (slot >= NSLOT) { slot -= NSLOT; ph ^= 1; }
        }

        if (ct == 128) { TL(3); TLMID(); }
        TW(0);
        {
            float u[2][8];
#pragma unroll
            for (int c = 0; c < 8; c++) {
                u[0][c] = acc[c][0] + acc[c ^ 1][1];
                u[1][c] = acc[c][2] + acc[c ^ 1][3];
            }
#pragma unroll
            for (int hf = 0; hf < 2; hf++) {
#pragma unroll
                for (int c = 0; c < 8; c++)
                    if (!(c & 2)) u[hf][c] += __shfl_xor_sync(0xffffffffu, u[hf][c ^ 2], 1);
                u[hf][0] += __shfl_xor_sync(0xffffffffu, u[hf][4], 2);
                u[hf][1] += __shfl_xor_sync(0xffffffffu, u[hf][5], 2);
                red[cw * DH + 64 * hf + 16 * t + g] = u[hf][0];
                red[cw * DH + 64 * hf + 16 * t + 8 + g] = u[hf][1];
            }
            const float lw = warp_sum(l_run);
            if (lane == 0) reinterpret_cast<float2*>(smem + SM_ML)[cw] = make_float2(m_run, lw);
        }
        TW(1);
        named_sync(1, NCW * 32);
        TW(2);

        if (ct < DH) {
            const float2* ml = reinterpret_cast<const float2*>(smem + SM_ML);
            float M = ml[0].x;
#pragma unroll
            for (int w = 1; w < NCW; w++) M = fmaxf(M, ml[w].x);
            float o = 0.f, L = 0.f;
#pragma unroll
            for (int w = 0; w < NCW; w++) {
                const float e = ex2((ml[w].x - M) * LOG2E);
                o = fmaf(e, red[w * DH + ct], o);
                L = fmaf(e, ml[w].y, L);
            }
            ll_store(&g_scr.ox[head][split][ct], o, tag);
            if (ct == 0) ll_store(&g_scr.ox[head][split][DH], M, tag);
            if (ct == 1) ll_store(&g_scr.ox[head][split][DH + 1], L, tag);
        }

        if (ct == 0) TL(4);
        if (cw == 0) {
            unsigned long long wo4[SPLITS], wm[SPLITS], wl[SPLITS];
            uint32_t it = 0;
            bool ok;
            do {
                ok = true;
#pragma unroll
                for (int i = 0; i < SPLITS; i++) {
                    wo4[i] = ll_load(&g_scr.ox[head][i][split * WO_ROWS + lane]);
                    ll_load2(&g_scr.ox[head][i][DH], wm[i], wl[i]);
                }
#pragma unroll
                for (int i = 0; i < SPLITS; i++) ok = ok && ll_ok(wo4[i], tag) && ll_ok(wm[i], tag) && ll_ok(wl[i], tag);
                if (++it > SPIN_LIMIT) __trap();
            } while (!ok);
            float M = ll_val(wm[0]);
#pragma unroll
            for (int i = 1; i < SPLITS; i++) M = fmaxf(M, ll_val(wm[i]));
            float o = 0.f, L = 0.f;
#pragma unroll
            for (int i = 0; i < SPLITS; i++) {
                const float e = ex2((ll_val(wm[i]) - M) * LOG2E);
                o = fmaf(e, ll_val(wo4[i]), o);
                L = fmaf(e, ll_val(wl[i]), L);
            }
            reinterpret_cast<__nv_bfloat16*>(smem + SM_OB)[lane] = __float2bfloat16_rn(__fdiv_rn(o, L));
        }
        if (ct == 0) TL(5);
        mbar_wait(bar_w, 0);
        if (ct == 0) TL(6);
        named_sync(1, NCW * 32);
        TW(3);

        {
            const uint32_t* ob = reinterpret_cast<const uint32_t*>(smem + SM_OB);
            const uint32_t b00 = ob[t], b01 = ob[4 + t], b10 = ob[8 + t], b11 = ob[12 + t];
            float d[5][4];
            const uint32_t wa = sbase + SM_WBUF + (uint32_t)(rho + 8 * (mi >> 1)) * WO_PITCH + (uint32_t)(cw * 80 + 8 * (mi & 1)) * 2u;
#pragma unroll
            for (int i = 0; i < 5; i++) {
                d[i][0] = d[i][1] = d[i][2] = d[i][3] = 0.f;
                uint32_t r[4], u[4];
                ldsm_x4_t(r, wa + i * 32);
                ldsm_x4_t(u, wa + i * 32 + 16 * WO_PITCH);
                mma_bf16(d[i], r[0], r[1], r[2], r[3], b00, b01);
                mma_bf16(d[i], u[0], u[1], u[2], u[3], b10, b11);
            }
#pragma unroll
            for (int k = 0; k < 3; k++) {
                const int i0 = 2 * k, i1 = (2 * k + 1 < 5) ? 2 * k + 1 : 2 * k;
                const float v0 = (t & 1) ? d[i0][2] : d[i0][0];
                const float v1 = (t & 1) ? d[i1][2] : d[i1][0];
                const float v = (t >> 1) ? v1 : v0;
                const int tl = 2 * k + (t >> 1);
                if (tl < 5) ll_store(&g_scr.tx[cw * 10 + 2 * tl + (t & 1)][cta][g], v, tag);
            }
        }

        if (ct == 0) TL(7);
        TW(4);
        if (cta < NFIN) {
            const unsigned long long* src = &g_scr.tx[cta][ct >> 1][(ct & 1) * 4];
            unsigned long long w0, w1_, w2_, w3;
            uint32_t it = 0;
            bool ok;
            do {
                ll_load2(src, w0, w1_);
                ll_load2(src + 2, w2_, w3);
                ok = ll_ok(w0, tag) && ll_ok(w1_, tag) && ll_ok(w2_, tag) && ll_ok(w3, tag);
                if (++it > SPIN_LIMIT) __trap();
            } while (!ok);
            float v0 = ll_val(w0), v1 = ll_val(w1_), v2 = ll_val(w2_), v3 = ll_val(w3);
#pragma unroll
            for (int o = 2; o < 32; o <<= 1) {
                v0 += __shfl_xor_sync(0xffffffffu, v0, o);
                v1 += __shfl_xor_sync(0xffffffffu, v1, o);
                v2 += __shfl_xor_sync(0xffffffffu, v2, o);
                v3 += __shfl_xor_sync(0xffffffffu, v3, o);
            }
            if (ct == 0) TL(8);
            TW(5);
            if (lane < 2) {
                float4* dst = reinterpret_cast<float4*>(smem + SM_FIN) + cw * 2 + lane;
                *dst = make_float4(v0, v1, v2, v3);
            }
            named_sync(2, NCW * 32 + 32);
            TW(6);
            if (ct < 8) {
                const float* fin = reinterpret_cast<const float*>(smem + SM_FIN);
                float a = 0.f;
#pragma unroll
                for (int w = 0; w < NCW; w++) a += fin[w * 8 + ct];
                const int col = cta * 8 + ct;
                const float r = bf16r(bf_lo(xfin) + bf16r(a));
                out[col] = __float2bfloat16_rn(r + reinterpret_cast<const float*>(smem + SM_MLP)[ct]);
                if (ct == 0) { TL(9); TLEND(); }
                if (cta == 0 && ct == 0) *reinterpret_cast<volatile unsigned int*>(&g_scr.epoch) = tag;
            }
        }
    } else if (cta < NFIN) {
        float xv[20];
        unpack_x20(xraw, xv);
        float mean_b, den_b;
        ln_stats(xv, mean_b, den_b);
#pragma unroll
        for (int i = 0; i < 20; i++) xv[i] = ln_apply(xv[i], mean_b, den_b);
        float mean2, den2;
        ln_stats(xv, mean2, den2);
        float h[8], y[8];
#pragma unroll
        for (int j = 0; j < 8; j++) {
            const float xn = ln_apply(__bfloat162float(x[cta * 8 + j]), mean_b, den_b);
            h[j] = ln_apply(xn, mean2, den2);
            y[j] = 0.f;
        }
        const __nv_bfloat16* mw = reinterpret_cast<const __nv_bfloat16*>(smem + SM_MW);
        mbar_wait(bar_m, 0);
        for (int f = lane; f < FF; f += 32) {
            const float a = __bfloat162float(mw[f]), b = __bfloat162float(mw[FF + f]), c = __bfloat162float(mw[2 * FF + f]);
#pragma unroll
            for (int j = 0; j < 8; j++) {
                const float u = bf16r(bf16r(h[j] * a) + b);
                const float inner = 0.7978845608028654f * (u + 0.044715f * u * u * u);
                const float gl = bf16r(0.5f * u * (1.0f + tanhf(inner)));
                y[j] = fmaf(gl, c, y[j]);
            }
        }
        const float bias2 = __bfloat162float(b2[0]);
#pragma unroll
        for (int j = 0; j < 8; j++) {
            const float s = warp_sum(y[j]);
            if (lane == j) reinterpret_cast<float*>(smem + SM_MLP)[j] = bf16r(bf16r(s) + bias2);
        }
        __syncwarp();
        if (lane == 0) TL(10);
        named_arrive(2, NCW * 32 + 32);
    }
}

}

extern "C" void kernel_launch(void* const* d_in, const int* in_sizes, int n_in, void* d_out, int out_size) {
    (void)in_sizes; (void)n_in; (void)out_size;
    const __nv_bfloat16* x = (const __nv_bfloat16*)d_in[0];
    const __nv_bfloat16* kc = (const __nv_bfloat16*)d_in[1];
    const __nv_bfloat16* vc = (const __nv_bfloat16*)d_in[2];
    const __nv_bfloat16* wo = (const __nv_bfloat16*)d_in[4];
    const __nv_bfloat16* w1 = (const __nv_bfloat16*)d_in[6];
    const __nv_bfloat16* b1 = (const __nv_bfloat16*)d_in[7];
    const __nv_bfloat16* w2 = (const __nv_bfloat16*)d_in[8];
    const __nv_bfloat16* b2 = (const __nv_bfloat16*)d_in[9];

    static CUtensorMap tm_wq;
    static void* tm_ptr = nullptr;
    if (tm_ptr != d_in[3]) {
        typedef CUresult (*encode_fn)(CUtensorMap*, CUtensorMapDataType, cuuint32_t, void*, const cuuint64_t*,
                                      const cuuint64_t*, const cuuint32_t*, const cuuint32_t*, CUtensorMapInterleave,
                                      CUtensorMapSwizzle, CUtensorMapL2promotion, CUtensorMapFloatOOBfill);
        void* fn = nullptr;
        cudaDriverEntryPointQueryResult qr;
        cudaGetDriverEntryPoint("cuTensorMapEncodeTiled", &fn, cudaEnableDefault, &qr);
        const cuuint64_t gdim[2] = {(cuuint64_t)(NH * DH), (cuuint64_t)D_MODEL};
        const cuuint64_t gstride[1] = {(cuuint64_t)(NH * DH * 2)};
        const cuuint32_t box[2] = {(cuuint32_t)DH, (cuuint32_t)QROWS};
        const cuuint32_t estride[2] = {1, 1};
        ((encode_fn)fn)(&tm_wq, CU_TENSOR_MAP_DATA_TYPE_BFLOAT16, 2, d_in[3], gdim, gstride, box, estride,
                        CU_TENSOR_MAP_INTERLEAVE_NONE, CU_TENSOR_MAP_SWIZZLE_NONE, CU_TENSOR_MAP_L2_PROMOTION_NONE,
                        CU_TENSOR_MAP_FLOAT_OOB_FILL_NONE);
        cudaFuncSetAttribute(fused_decode_kernel, cudaFuncAttributeMaxDynamicSharedMemorySize, SM_TOTAL);
        tm_ptr = d_in[3];
    }
    fused_decode_kernel<<<NCTA, NTHREADS, SM_TOTAL, cudaStreamPerThread>>>(tm_wq, x, kc, vc, wo, w1, b1, w2, b2,
                                                                          (__nv_bfloat16*)d_out);
}
```

```cpp
#include <cuda_runtime.h>
#include <cuda.h>
#include <cuda_bf16.h>
#include <stdint.h>

namespace {

constexpr int D_MODEL = 640;
constexpr int NH = 32;
constexpr int SK = 32768;
constexpr int DH = 128;
constexpr int FF = 1728;

constexpr int SPLITS = 4;
constexpr int NCTA = NH * SPLITS;
constexpr int TILE_KEYS = 128;
constexpr int STAGE_BYTES = TILE_KEYS * DH * 2;
constexpr int NTILES = SK / SPLITS / TILE_KEYS;
constexpr int NITEMS = 2 * NTILES;
constexpr int NSTAGE = 6;

#define FILL_W 4
constexpr int FILL_WINDOW = FILL_W;

constexpr int QROWS = D_MODEL / SPLITS;
constexpr int WO_ROWS = DH / SPLITS;
constexpr int WO_ROW_BYTES = D_MODEL * 2;
constexpr int WO_PITCH = WO_ROW_BYTES + 16;
constexpr int NFIN = D_MODEL / 8;

constexpr int NCW = 8;
constexpr int NTHREADS = 32 * (NCW + 2);

constexpr int W_STAGE = NSTAGE - 1;
constexpr int SM_W = W_STAGE * STAGE_BYTES;
constexpr int W_BYTES = WO_ROWS * WO_PITCH;
constexpr int SM_RED = SM_W + W_BYTES;
constexpr int SM_ML = SM_RED + NCW * DH * 4;
constexpr int SM_QS = SM_ML + NCW * 8;
constexpr int SM_OB = SM_QS + DH * 2;
constexpr int SM_FIN = SM_OB + WO_ROWS * 2;
constexpr int SM_MLP = SM_FIN + NCW * 8 * 4;
constexpr int SM_MW = SM_MLP + 8 * 4;
constexpr int SM_BAR = SM_MW + 3 * FF * 2;
constexpr int SM_TOTAL = SM_BAR + (2 * NSTAGE + 4) * 8;
static_assert(SM_MW % 16 == 0 && SM_BAR % 8 == 0 && SM_RED % 16 == 0, "alignment");
static_assert(W_BYTES >= STAGE_BYTES && W_BYTES >= QROWS * DH * 2, "weight buffer");
constexpr int LAST_W = ((NITEMS - 1 - W_STAGE) / NSTAGE) * NSTAGE + W_STAGE;
static_assert(LAST_W < NITEMS - 2, "wo must not wait for the last tile");

constexpr float LOG2E = 1.4426950408889634f;
constexpr float SM_SCALE = 0.08838834764831845f;
constexpr float LN_EPS = 1e-5f;
constexpr uint32_t SPIN_LIMIT = 1u << 24;

struct Scratch {
    unsigned long long qx[NH][SPLITS][DH];
    unsigned long long ox[NH][SPLITS][DH + 8];
    unsigned long long tx[NFIN][NCTA][8];
    unsigned int epoch;
};
__device__ __align__(128) Scratch g_scr;

#define TL(i) do { } while (0)
#define TW(i) do { } while (0)
#define TL0() do { } while (0)
#define TLMID() do { } while (0)
#define TLEND() do { } while (0)

__device__ __forceinline__ uint32_t smem_u32(const void* p) { return (uint32_t)__cvta_generic_to_shared(p); }

__device__ __forceinline__ void mbar_init(uint32_t bar, uint32_t cnt) {
    asm volatile("mbarrier.init.shared::cta.b64 [%0], %1;" ::"r"(bar), "r"(cnt) : "memory");
}
__device__ __forceinline__ void mbar_expect_tx(uint32_t bar, uint32_t bytes) {
    asm volatile("mbarrier.arrive.expect_tx.shared::cta.b64 _, [%0], %1;" ::"r"(bar), "r"(bytes) : "memory");
}
__device__ __forceinline__ void mbar_arrive(uint32_t bar) {
    asm volatile("mbarrier.arrive.shared::cta.b64 _, [%0];" ::"r"(bar) : "memory");
}
__device__ __forceinline__ void mbar_wait(uint32_t bar, uint32_t parity) {
    uint32_t done, it = 0;
    do {
        asm volatile(
            "{\n.reg .pred p;\n"
            "mbarrier.try_wait.parity.shared::cta.b64 p, [%1], %2;\n"
            "selp.u32 %0, 1, 0, p;\n}"
            : "=r"(done) : "r"(bar), "r"(parity) : "memory");
        if (++it > SPIN_LIMIT) __trap();
    } while (!done);
}
__device__ __forceinline__ void bulk_load(uint32_t dst, const void* src, uint32_t bytes, uint32_t bar) {
    asm volatile("cp.async.bulk.shared::cluster.global.mbarrier::complete_tx::bytes [%0], [%1], %2, [%3];"
                 ::"r"(dst), "l"(src), "r"(bytes), "r"(bar) : "memory");
}
__device__ __forceinline__ void bulk_load_stream(uint32_t dst, const void* src, uint32_t bytes, uint32_t bar, uint64_t pol) {
    asm volatile("cp.async.bulk.shared::cluster.global.mbarrier::complete_tx::bytes.L2::cache_hint [%0], [%1], %2, [%3], %4;"
                 ::"r"(dst), "l"(src), "r"(bytes), "r"(bar), "l"(pol) : "memory");
}
__device__ __forceinline__ void ldsm_x4(uint32_t (&r)[4], uint32_t addr) {
    asm volatile("ldmatrix.sync.aligned.m8n8.x4.shared.b16 {%0,%1,%2,%3}, [%4];"
                 : "=r"(r[0]), "=r"(r[1]), "=r"(r[2]), "=r"(r[3]) : "r"(addr) : "memory");
}
__device__ __forceinline__ void ldsm_x4_t(uint32_t (&r)[4], uint32_t addr) {
    asm volatile("ldmatrix.sync.aligned.m8n8.x4.trans.shared.b16 {%0,%1,%2,%3}, [%4];"
                 : "=r"(r[0]), "=r"(r[1]), "=r"(r[2]), "=r"(r[3]) : "r"(addr) : "memory");
}
__device__ __forceinline__ void mma_bf16(float (&d)[4], const uint32_t (&a)[4], uint32_t b0, uint32_t b1) {
    asm volatile("mma.sync.aligned.m16n8k16.row.col.f32.bf16.bf16.f32 {%0,%1,%2,%3}, {%4,%5,%6,%7}, {%8,%9}, {%0,%1,%2,%3};"
                 : "+f"(d[0]), "+f"(d[1]), "+f"(d[2]), "+f"(d[3])
                 : "r"(a[0]), "r"(a[1]), "r"(a[2]), "r"(a[3]), "r"(b0), "r"(b1));
}
__device__ __forceinline__ float ex2(float x) {
    float y;
    asm("ex2.approx.ftz.f32 %0, %1;" : "=f"(y) : "f"(x));
    return y;
}
__device__ __forceinline__ float bf16r(float x) { return __bfloat162float(__float2bfloat16_rn(x)); }
__device__ __forceinline__ float bf_lo(uint32_t u) { return __uint_as_float(u << 16); }
__device__ __forceinline__ float bf_hi(uint32_t u) { return __uint_as_float(u & 0xffff0000u); }
__device__ __forceinline__ uint32_t pack_bf16(float lo, float hi) {
    uint32_t r;
    asm("cvt.rn.bf16x2.f32 %0, %1, %2;" : "=r"(r) : "f"(hi), "f"(lo));
    return r;
}
__device__ __forceinline__ void named_sync(int id, int n) { asm volatile("bar.sync %0, %1;" ::"r"(id), "r"(n) : "memory"); }
__device__ __forceinline__ void named_arrive(int id, int n) { asm volatile("bar.arrive %0, %1;" ::"r"(id), "r"(n) : "memory"); }

__device__ __forceinline__ void ll_store(unsigned long long* p, float v, uint32_t tag) {
    unsigned long long w = ((unsigned long long)tag << 32) | (unsigned long long)__float_as_uint(v);
    asm volatile("st.relaxed.gpu.global.b64 [%0], %1;" ::"l"(p), "l"(w) : "memory");
}
__device__ __forceinline__ unsigned long long ll_load(const unsigned long long* p) {
    unsigned long long w;
    asm volatile("ld.relaxed.gpu.global.b64 %0, [%1];" : "=l"(w) : "l"(p) : "memory");
    return w;
}
__device__ __forceinline__ void ll_load2(const unsigned long long* p, unsigned long long& a, unsigned long long& b) {
    asm volatile("ld.relaxed.gpu.global.v2.b64 {%0,%1}, [%2];" : "=l"(a), "=l"(b) : "l"(p) : "memory");
}
__device__ __forceinline__ bool ll_ok(unsigned long long w, uint32_t tag) { return (uint32_t)(w >> 32) == tag; }
__device__ __forceinline__ float ll_val(unsigned long long w) { return __uint_as_float((uint32_t)w); }

__device__ __forceinline__ float warp_sum(float v) {
#pragma unroll
    for (int o = 16; o > 0; o >>= 1) v += __shfl_xor_sync(0xffffffffu, v, o);
    return v;
}
__device__ __forceinline__ float warp_max(float v) {
#pragma unroll
    for (int o = 16; o > 0; o >>= 1) v = fmaxf(v, __shfl_xor_sync(0xffffffffu, v, o));
    return v;
}
__device__ __forceinline__ uint2 ldg_u64(const void* p) {
    uint2 v;
    asm volatile("ld.global.nc.v2.u32 {%0,%1}, [%2];" : "=r"(v.x), "=r"(v.y) : "l"(p));
    return v;
}
__device__ __forceinline__ uint32_t ldg_u16(const void* p) {
    uint16_t v;
    asm volatile("ld.global.nc.u16 %0, [%1];" : "=h"(v) : "l"(p));
    return v;
}
__device__ __forceinline__ void unpack_x20(const uint2 (&u)[5], float (&v)[20]) {
#pragma unroll
    for (int i = 0; i < 5; i++) {
        v[4 * i + 0] = bf_lo(u[i].x); v[4 * i + 1] = bf_hi(u[i].x);
        v[4 * i + 2] = bf_lo(u[i].y); v[4 * i + 3] = bf_hi(u[i].y);
    }
}

__device__ __forceinline__ void ln_stats(const float (&v)[20], float& mean_b, float& den_b) {
    float s = 0.f;
#pragma unroll
    for (int i = 0; i < 20; i++) s += v[i];
    const float mean = warp_sum(s) * (1.0f / D_MODEL);
    float q = 0.f;
#pragma unroll
    for (int i = 0; i < 20; i++) { const float d = v[i] - mean; q = fmaf(d, d, q); }
    const float var = warp_sum(q) * (1.0f / D_MODEL);
    mean_b = bf16r(mean);
    den_b = bf16r(sqrtf(bf16r(bf16r(var) + LN_EPS)));
}
__device__ __forceinline__ float ln_apply(float x, float mean_b, float den_b) {
    return bf16r(__fdiv_rn(bf16r(x - mean_b), den_b));
}

__global__ void __launch_bounds__(NTHREADS, 1)
fused_decode_kernel(const __grid_constant__ CUtensorMap tm_wq,
                    const __nv_bfloat16* __restrict__ x, const __nv_bfloat16* __restrict__ kc,
                    const __nv_bfloat16* __restrict__ vc, const __nv_bfloat16* __restrict__ wo,
                    const __nv_bfloat16* __restrict__ w1, const __nv_bfloat16* __restrict__ b1,
                    const __nv_bfloat16* __restrict__ w2, const __nv_bfloat16* __restrict__ b2,
                    __nv_bfloat16* __restrict__ out)
{
    extern __shared__ __align__(1024) uint8_t smem[];
    const uint32_t sbase = smem_u32(smem);
    const int tid = threadIdx.x, warp = tid >> 5, lane = tid & 31;
    const int cta = blockIdx.x, head = cta / SPLITS, split = cta % SPLITS;
    const uint32_t bar_full = sbase + SM_BAR, bar_empty = bar_full + NSTAGE * 8, bar_w = bar_empty + NSTAGE * 8,
                   bar_m = bar_w + 8, bar_q = bar_m + 8, bar_qd = bar_q + 8;

    if (tid == 32) TL0();

    const size_t kv_off = ((size_t)head * SK + (size_t)split * TILE_KEYS) * (DH * 2);
    const uint8_t* kbase = reinterpret_cast<const uint8_t*>(kc) + kv_off;
    const uint8_t* vbase = reinterpret_cast<const uint8_t*>(vc) + kv_off;
    uint64_t pol = 0;

    uint2 xraw[5];
    uint32_t xrow[10];
    uint32_t epoch = 0, xfin = 0;
    if (warp == 0) {
        if (lane == 0) {
            asm volatile("prefetch.tensormap [%0];" ::"l"(&tm_wq) : "memory");
            mbar_init(bar_q, 1);
            asm volatile("fence.proxy.async.shared::cta;" ::: "memory");
            mbar_expect_tx(bar_q, QROWS * DH * 2);
            asm volatile("cp.async.bulk.tensor.2d.shared::cluster.global.mbarrier::complete_tx::bytes [%0], [%1, {%3, %4}], [%2];"
                         ::"r"(sbase + SM_W), "l"(&tm_wq), "r"(bar_q), "r"(head * DH), "r"(split * QROWS) : "memory");
            TL(18);
            for (int s = 0; s < NSTAGE; s++) {
                mbar_init(bar_full + s * 8, 1);
                mbar_init(bar_empty + s * 8, NCW);
            }
            mbar_init(bar_w, 1);
            mbar_init(bar_m, 1);
            mbar_init(bar_qd, NCW);
            asm volatile("fence.proxy.async.shared::cta;" ::: "memory");
            asm volatile("createpolicy.fractional.L2::evict_first.b64 %0, 1.0;" : "=l"(pol));
            for (int i = 0; i < FILL_WINDOW; i++) {
                mbar_expect_tx(bar_full + i * 8, STAGE_BYTES);
                bulk_load_stream(sbase + i * STAGE_BYTES, ((i & 1) ? vbase : kbase) + (size_t)(i >> 1) * (SPLITS * STAGE_BYTES),
                                 STAGE_BYTES, bar_full + i * 8, pol);
            }
            TL(15);
        }
        __syncwarp();
        asm volatile("ld.volatile.global.u32 %0, [%1];" : "=r"(epoch) : "l"(&g_scr.epoch) : "memory");
    } else {
        if (warp <= NCW) {
            const int ct = tid - 32;
            asm volatile("ld.volatile.global.u32 %0, [%1];" : "=r"(epoch) : "l"(&g_scr.epoch) : "memory");
#pragma unroll
            for (int i = 0; i < 10; i++) xrow[i] = ldg_u16(x + split * QROWS + (ct >> 4) + 16 * i);
            xfin = ldg_u16(x + (cta < NFIN ? cta * 8 : 0) + (ct & 7));
        }
#pragma unroll
        for (int i = 0; i < 5; i++) xraw[i] = ldg_u64(reinterpret_cast<const uint2*>(x) + lane + 32 * i);
        if (tid == 32) TL(16);
        if (warp <= NCW) {
            const int ct = tid - 32;
            if (ct < DH) ll_store(&g_scr.qx[head][split][ct], 0.f, 0u);
            if (ct < DH + 8) ll_store(&g_scr.ox[head][split][ct], 0.f, 0u);
#pragma unroll
            for (int k = 0; k < 3; k++) {
                const int idx = ct + 256 * k;
                if (idx < D_MODEL) ll_store(&g_scr.tx[idx >> 3][cta][idx & 7], 0.f, 0u);
            }
        }
    }
    if (tid == 32) TL(17);
    __syncthreads();

    if (warp == 0) {
        if (lane == 0) {
            for (int i = FILL_WINDOW; i < NSTAGE; i++) {
                mbar_wait(bar_full + (i - FILL_WINDOW) * 8, 0);
                if (i == W_STAGE) mbar_wait(bar_qd, 0);
                mbar_expect_tx(bar_full + i * 8, STAGE_BYTES);
                bulk_load_stream(sbase + i * STAGE_BYTES, ((i & 1) ? vbase : kbase) + (size_t)(i >> 1) * (SPLITS * STAGE_BYTES),
                                 STAGE_BYTES, bar_full + i * 8, pol);
            }
            if (cta < NFIN) {
                mbar_expect_tx(bar_m, 3 * FF * 2);
                bulk_load(sbase + SM_MW, w1, FF * 2, bar_m);
                bulk_load(sbase + SM_MW + FF * 2, b1, FF * 2, bar_m);
                bulk_load(sbase + SM_MW + 2 * FF * 2, w2, FF * 2, bar_m);
            }
            int slot = 0;
            uint32_t ph = 0;
            for (int i = NSTAGE; i < NITEMS; i++) {
                mbar_wait(bar_empty + slot * 8, ph);
                mbar_expect_tx(bar_full + slot * 8, STAGE_BYTES);
                bulk_load_stream(sbase + slot * STAGE_BYTES, ((i & 1) ? vbase : kbase) + (size_t)(i >> 1) * (SPLITS * STAGE_BYTES),
                                 STAGE_BYTES, bar_full + slot * 8, pol);
                if (++slot == NSTAGE) { slot = 0; ph ^= 1; }
            }
            TL(11);
            mbar_wait(bar_empty + W_STAGE * 8, (LAST_W / NSTAGE) & 1);
            mbar_expect_tx(bar_w, WO_ROWS * WO_ROW_BYTES);
        }
        __syncwarp();
        bulk_load(sbase + SM_W + lane * WO_PITCH,
                  wo + (size_t)(head * DH + split * WO_ROWS + lane) * D_MODEL, WO_ROW_BYTES, bar_w);

        {
            const uint32_t tag = epoch + 1u;
            unsigned long long wo4[SPLITS], wm[SPLITS], wl[SPLITS];
            uint32_t it = 0;
            bool ok;
            do {
                ok = true;
#pragma unroll
                for (int i = 0; i < SPLITS; i++) {
                    wo4[i] = ll_load(&g_scr.ox[head][i][split * WO_ROWS + lane]);
                    ll_load2(&g_scr.ox[head][i][DH], wm[i], wl[i]);
                }
#pragma unroll
                for (int i = 0; i < SPLITS; i++) ok = ok && ll_ok(wo4[i], tag) && ll_ok(wm[i], tag) && ll_ok(wl[i], tag);
                if (++it > SPIN_LIMIT) __trap();
            } while (!ok);
            float M = ll_val(wm[0]);
#pragma unroll
            for (int i = 1; i < SPLITS; i++) M = fmaxf(M, ll_val(wm[i]));
            float o = 0.f, L = 0.f;
#pragma unroll
            for (int i = 0; i < SPLITS; i++) {
                const float e = ex2((ll_val(wm[i]) - M) * LOG2E);
                o = fmaf(e, ll_val(wo4[i]), o);
                L = fmaf(e, ll_val(wl[i]), L);
            }
            reinterpret_cast<__nv_bfloat16*>(smem + SM_OB)[lane] = __float2bfloat16_rn(__fdiv_rn(o, L));
            if (lane == 0) TL(5);
            __syncwarp();
            named_arrive(3, NCW * 32 + 32);
        }
    } else if (warp <= NCW) {
        const int cw = warp - 1, ct = tid - 32;
        const int g = lane >> 2, t = lane & 3;
        float* red = reinterpret_cast<float*>(smem + SM_RED);
        const uint32_t tag = epoch + 1u;

        {
            float xv[20];
            unpack_x20(xraw, xv);
            float mean_b, den_b;
            ln_stats(xv, mean_b, den_b);
            if (ct == 0) TL(12);
            float a[8];
#pragma unroll
            for (int j = 0; j < 8; j++) a[j] = 0.f;
            float xn[10];
#pragma unroll
            for (int i = 0; i < 10; i++) xn[i] = ln_apply(bf_lo(xrow[i]), mean_b, den_b);
            mbar_wait(bar_q, 0);
            if (ct == 0) TL(19);
            const uint4* wsm = reinterpret_cast<const uint4*>(smem + SM_W) + ct;
#pragma unroll
            for (int i = 0; i < 10; i++) {
                const uint4 w = wsm[i * 256];
                a[0] = fmaf(xn[i], bf_lo(w.x), a[0]); a[1] = fmaf(xn[i], bf_hi(w.x), a[1]);
                a[2] = fmaf(xn[i], bf_lo(w.y), a[2]); a[3] = fmaf(xn[i], bf_hi(w.y), a[3]);
                a[4] = fmaf(xn[i], bf_lo(w.z), a[4]); a[5] = fmaf(xn[i], bf_hi(w.z), a[5]);
                a[6] = fmaf(xn[i], bf_lo(w.w), a[6]); a[7] = fmaf(xn[i], bf_hi(w.w), a[7]);
            }
            __syncwarp();
            if (lane == 0) mbar_arrive(bar_qd);
#pragma unroll
            for (int j = 0; j < 8; j++) a[j] += __shfl_xor_sync(0xffffffffu, a[j], 16);
            if (lane < 16) {
                float4* dst = reinterpret_cast<float4*>(red + cw * DH + lane * 8);
                dst[0] = make_float4(a[0], a[1], a[2], a[3]);
                dst[1] = make_float4(a[4], a[5], a[6], a[7]);
            }
            named_sync(1, NCW * 32);
            if (ct == 0) TL(1);
            if (ct < DH) {
                float s = 0.f;
#pragma unroll
                for (int w = 0; w < NCW; w++) s += red[w * DH + ct];
                ll_store(&g_scr.qx[head][split][ct], s, tag);
                unsigned long long w4[SPLITS];
                uint32_t it = 0;
                bool ok;
                do {
#pragma unroll
                    for (int i = 0; i < SPLITS; i++) w4[i] = ll_load(&g_scr.qx[head][i][ct]);
                    ok = true;
#pragma unroll
                    for (int i = 0; i < SPLITS; i++) ok = ok && ll_ok(w4[i], tag);
                    if (++it > SPIN_LIMIT) __trap();
                } while (!ok);
                const float q = (ll_val(w4[0]) + ll_val(w4[1])) + (ll_val(w4[2]) + ll_val(w4[3]));
                reinterpret_cast<__nv_bfloat16*>(smem + SM_QS)[ct] = __float2bfloat16_rn(q);
            }
            named_sync(1, NCW * 32);
            if (ct == 0) TL(2);
        }

        uint32_t qf[8][2];
#pragma unroll
        for (int s = 0; s < 8; s++) {
            const uint32_t* qs = reinterpret_cast<const uint32_t*>(smem + SM_QS);
            qf[s][0] = qs[4 * (s ^ g) + t];
            qf[s][1] = qs[32 + 4 * (s ^ g) + t];
        }

        float acc[8][4];
#pragma unroll
        for (int c = 0; c < 8; c++) { acc[c][0] = acc[c][1] = acc[c][2] = acc[c][3] = 0.f; }
        float m_run = -INFINITY, l_run = 0.f;
        const bool valid = (t == (g >> 1));
        const bool odd = g & 1;
        const uint32_t sel0 = odd ? 0x1044u : 0x4410u;
        const uint32_t sel1 = odd ? 0x3244u : 0x4432u;
        const int mi = lane >> 3, rho = lane & 7;
        const uint32_t k_off = (uint32_t)(cw * 16 + rho + 8 * (mi & 1)) * 256u + (uint32_t)(mi >> 1) * 128u + (uint32_t)rho * 16u;
        const uint32_t v_off = (uint32_t)(cw * 16 + rho + 8 * (mi >> 1)) * 256u + (uint32_t)(mi & 1) * 128u + (uint32_t)rho * 16u;

        int slot = 0;
        uint32_t ph = 0;
#pragma unroll 1
        for (int tile = 0; tile < NTILES; tile++) {
            const uint32_t ka = sbase + slot * STAGE_BYTES + k_off;
            const uint32_t va = sbase + (slot + 1) * STAGE_BYTES + v_off;

            mbar_wait(bar_full + slot * 8, ph);
            if (ct == 0 && tile == 0) TL(13);
            if (ct == 0 && tile == 3) TL(14);
            float s0[4] = {0.f, 0.f, 0.f, 0.f}, s1[4] = {0.f, 0.f, 0.f, 0.f};
#pragma unroll
            for (int s = 0; s < 8; s += 2) {
                uint32_t r[4], u[4];
                ldsm_x4(r, ka ^ (uint32_t)(s << 4));
                ldsm_x4(u, ka ^ (uint32_t)((s + 1) << 4));
                mma_bf16(s0, r, qf[s][0], qf[s][1]);
                mma_bf16(s1, u, qf[s + 1][0], qf[s + 1][1]);
            }
            __syncwarp();
            if (lane == 0) mbar_arrive(bar_empty + slot * 8);

            float sa = odd ? (s0[1] + s1[1]) : (s0[0] + s1[0]);
            float sb = odd ? (s0[3] + s1[3]) : (s0[2] + s1[2]);
            sa = valid ? bf16r(bf16r(sa) * SM_SCALE) : -INFINITY;
            sb = valid ? bf16r(bf16r(sb) * SM_SCALE) : -INFINITY;
            const float smax = fmaxf(sa, sb);
            const bool last = tile == NTILES - 1;
            if (__any_sync(0xffffffffu, smax > m_run) || last) {
                float m_new = fmaxf(m_run, warp_max(smax));
                if (last) {
                    float* mw = reinterpret_cast<float*>(smem + SM_ML);
                    if (lane == 0) mw[cw] = m_new;
                    named_sync(1, NCW * 32);
                    const float4 ma = *reinterpret_cast<const float4*>(mw), mb = *reinterpret_cast<const float4*>(mw + 4);
                    m_new = fmaxf(fmaxf(fmaxf(ma.x, ma.y), fmaxf(ma.z, ma.w)), fmaxf(fmaxf(mb.x, mb.y), fmaxf(mb.z, mb.w)));
                }
                const float sc = ex2((m_run - m_new) * LOG2E);
#pragma unroll
                for (int c = 0; c < 8; c++) { acc[c][0] *= sc; acc[c][1] *= sc; acc[c][2] *= sc; acc[c][3] *= sc; }
                l_run *= sc;
                m_run = m_new;
            }
            const float pa = ex2((sa - m_run) * LOG2E);
            const float pb = ex2((sb - m_run) * LOG2E);
            l_run += pa + pb;
            if (last) {
                const float lw = warp_sum(l_run);
                if (lane == 0) reinterpret_cast<float*>(smem + SM_ML)[NCW + cw] = lw;
            }
            const uint32_t pk = pack_bf16(pa, pb);
            const uint32_t b0 = __byte_perm(pk, 0u, sel0);
            const uint32_t b1 = __byte_perm(pk, 0u, sel1);

            mbar_wait(bar_full + (slot + 1) * 8, ph);
#pragma unroll
            for (int c = 0; c < 8; c++) {
                uint32_t r[4];
                ldsm_x4_t(r, va ^ (uint32_t)(c << 4));
                mma_bf16(acc[c], r, b0, b1);
            }
            __syncwarp();
            if (lane == 0) mbar_arrive(bar_empty + (slot + 1) * 8);

            slot += 2;
            if (slot == NSTAGE) { slot = 0; ph ^= 1; }
        }
        if (ct == 128) { TL(3); TLMID(); }
        TW(0);

        {
            float u[2][8];
#pragma unroll
            for (int c = 0; c < 8; c++) {
                u[0][c] = acc[c][0] + acc[c ^ 1][1];
                u[1][c] = acc[c][2] + acc[c ^ 1][3];
            }
#pragma unroll
            for (int hf = 0; hf < 2; hf++) {
#pragma unroll
                for (int c = 0; c < 8; c++)
                    if (!(c & 2)) u[hf][c] += __shfl_xor_sync(0xffffffffu, u[hf][c ^ 2], 1);
                u[hf][0] += __shfl_xor_sync(0xffffffffu, u[hf][4], 2);
                u[hf][1] += __shfl_xor_sync(0xffffffffu, u[hf][5], 2);
                red[cw * DH + 64 * hf + 16 * t + g] = u[hf][0];
                red[cw * DH + 64 * hf + 16 * t + 8 + g] = u[hf][1];
            }
        }
        TW(1);
        named_sync(1, NCW * 32);
        TW(2);

        if (ct < DH) {
            const float o = ((red[ct] + red[DH + ct]) + (red[2 * DH + ct] + red[3 * DH + ct])) +
                            ((red[4 * DH + ct] + red[5 * DH + ct]) + (red[6 * DH + ct] + red[7 * DH + ct]));
            ll_store(&g_scr.ox[head][split][ct], o, tag);
        } else if (ct == DH) {
            const float4 la = *reinterpret_cast<const float4*>(smem + SM_ML + NCW * 4);
            const float4 lb = *reinterpret_cast<const float4*>(smem + SM_ML + NCW * 4 + 16);
            ll_store(&g_scr.ox[head][split][DH], m_run, tag);
            ll_store(&g_scr.ox[head][split][DH + 1], ((la.x + la.y) + (la.z + la.w)) + ((lb.x + lb.y) + (lb.z + lb.w)), tag);
        }
        if (ct == 0) TL(4);

        unsigned long long* txp = &g_scr.tx[cw * 10 + (t & 1) + 2 * (t >> 1)][cta][g];
        const uint32_t wa = sbase + SM_W + (uint32_t)(rho + 8 * (mi >> 1)) * WO_PITCH + (uint32_t)(cw * 80 + 8 * (mi & 1)) * 2u;
        mbar_wait(bar_w, 0);
        if (ct == 0) TL(6);
        uint32_t wf[5][2][4];
#pragma unroll
        for (int i = 0; i < 5; i++) {
            ldsm_x4_t(wf[i][0], wa + i * 32);
            ldsm_x4_t(wf[i][1], wa + i * 32 + 16 * WO_PITCH);
        }
        named_sync(3, NCW * 32 + 32);
        TW(3);

        {
            const uint32_t* ob = reinterpret_cast<const uint32_t*>(smem + SM_OB);
            const uint32_t b00 = ob[t], b01 = ob[4 + t], b10 = ob[8 + t], b11 = ob[12 + t];
            float d[5][4];
#pragma unroll
            for (int i = 0; i < 5; i++) {
                d[i][0] = d[i][1] = d[i][2] = d[i][3] = 0.f;
                mma_bf16(d[i], wf[i][0], b00, b01);
                mma_bf16(d[i], wf[i][1], b10, b11);
            }
#pragma unroll
            for (int k = 0; k < 3; k++) {
                const int i0 = 2 * k, i1 = (2 * k + 1 < 5) ? 2 * k + 1 : 2 * k;
                const float v0 = (t & 1) ? d[i0][2] : d[i0][0];
                const float v1 = (t & 1) ? d[i1][2] : d[i1][0];
                const float v = (t >> 1) ? v1 : v0;
                if (k < 2 || t < 2) ll_store(txp + (size_t)(4 * k) * NCTA * 8, v, tag);
            }
        }
        if (ct == 0) TL(7);
        TW(4);

        if (cta < NFIN) {
            const unsigned long long* src = &g_scr.tx[cta][ct >> 1][(ct & 1) * 4];
            unsigned long long w0, w1_, w2_, w3;
            uint32_t it = 0;
            bool ok;
            do {
                ll_load2(src, w0, w1_);
                ll_load2(src + 2, w2_, w3);
                ok = ll_ok(w0, tag) && ll_ok(w1_, tag) && ll_ok(w2_, tag) && ll_ok(w3, tag);
                if (++it > SPIN_LIMIT) __trap();
            } while (!ok);
            if (ct == 0) TL(8);
            TW(5);
            float v0 = ll_val(w0), v1 = ll_val(w1_), v2 = ll_val(w2_), v3 = ll_val(w3);
            const bool b1 = lane & 2, b2 = lane & 4;
            float k0 = b1 ? v2 : v0, k1 = b1 ? v3 : v1;
            k0 += __shfl_xor_sync(0xffffffffu, b1 ? v0 : v2, 2);
            k1 += __shfl_xor_sync(0xffffffffu, b1 ? v1 : v3, 2);
            float k = b2 ? k1 : k0;
            k += __shfl_xor_sync(0xffffffffu, b2 ? k0 : k1, 4);
            k += __shfl_xor_sync(0xffffffffu, k, 8);
            k += __shfl_xor_sync(0xffffffffu, k, 16);
            if (lane < 8)
                reinterpret_cast<float*>(smem + SM_FIN)[cw * 8 + 4 * (lane & 1) + (lane & 2) + (lane >> 2)] = k;
            named_sync(2, NCW * 32 + 32);
            TW(6);
            if (ct < 8) {
                const float* fin = reinterpret_cast<const float*>(smem + SM_FIN);
                float a = 0.f;
#pragma unroll
                for (int w = 0; w < NCW; w++) a += fin[w * 8 + ct];
                const float r = bf16r(bf_lo(xfin) + bf16r(a));
                out[cta * 8 + ct] = __float2bfloat16_rn(r + reinterpret_cast<const float*>(smem + SM_MLP)[ct]);
                if (ct == 0) { TL(9); TLEND(); }
                if (cta == 0 && ct == 0) *reinterpret_cast<volatile unsigned int*>(&g_scr.epoch) = tag;
            }
        }
    } else if (cta < NFIN) {
        float xv[20];
        unpack_x20(xraw, xv);
        float mean_b, den_b;
        ln_stats(xv, mean_b, den_b);
#pragma unroll
        for (int i = 0; i < 20; i++) xv[i] = ln_apply(xv[i], mean_b, den_b);
        float mean2, den2;
        ln_stats(xv, mean2, den2);
        float h[8], y[8];
#pragma unroll
        for (int j = 0; j < 8; j++) {
            const float xn = ln_apply(__bfloat162float(x[cta * 8 + j]), mean_b, den_b);
            h[j] = ln_apply(xn, mean2, den2);
            y[j] = 0.f;
        }
        const __nv_bfloat16* mw = reinterpret_cast<const __nv_bfloat16*>(smem + SM_MW);
        mbar_wait(bar_m, 0);
        for (int f = lane; f < FF; f += 32) {
            const float a = __bfloat162float(mw[f]), b = __bfloat162float(mw[FF + f]), c = __bfloat162float(mw[2 * FF + f]);
#pragma unroll
            for (int j = 0; j < 8; j++) {
                const float u = bf16r(bf16r(h[j] * a) + b);
                const float inner = 0.7978845608028654f * (u + 0.044715f * u * u * u);
                const float gl = bf16r(0.5f * u * (1.0f + tanhf(inner)));
                y[j] = fmaf(gl, c, y[j]);
            }
        }
        const float bias2 = __bfloat162float(b2[0]);
#pragma unroll
        for (int j = 0; j < 8; j++) {
            const float s = warp_sum(y[j]);
            if (lane == j) reinterpret_cast<float*>(smem + SM_MLP)[j] = bf16r(bf16r(s) + bias2);
        }
        __syncwarp();
        if (lane == 0) TL(10);
        named_arrive(2, NCW * 32 + 32);
    }
}

}

extern "C" void kernel_launch(void* const* d_in, const int* in_sizes, int n_in, void* d_out, int out_size) {
    (void)in_sizes; (void)n_in; (void)out_size;
    const __nv_bfloat16* x = (const __nv_bfloat16*)d_in[0];
    const __nv_bfloat16* kc = (const __nv_bfloat16*)d_in[1];
    const __nv_bfloat16* vc = (const __nv_bfloat16*)d_in[2];
    const __nv_bfloat16* wo = (const __nv_bfloat16*)d_in[4];
    const __nv_bfloat16* w1 = (const __nv_bfloat16*)d_in[6];
    const __nv_bfloat16* b1 = (const __nv_bfloat16*)d_in[7];
    const __nv_bfloat16* w2 = (const __nv_bfloat16*)d_in[8];
    const __nv_bfloat16* b2 = (const __nv_bfloat16*)d_in[9];

    static CUtensorMap tm_wq;
    static void* tm_ptr = nullptr;
    if (tm_ptr != d_in[3]) {
        typedef CUresult (*encode_fn)(CUtensorMap*, CUtensorMapDataType, cuuint32_t, void*, const cuuint64_t*,
                                      const cuuint64_t*, const cuuint32_t*, const cuuint32_t*, CUtensorMapInterleave,
                                      CUtensorMapSwizzle, CUtensorMapL2promotion, CUtensorMapFloatOOBfill);
        void* fn = nullptr;
        cudaDriverEntryPointQueryResult qr;
        cudaGetDriverEntryPoint("cuTensorMapEncodeTiled", &fn, cudaEnableDefault, &qr);
        const cuuint64_t gdim[2] = {(cuuint64_t)(NH * DH), (cuuint64_t)D_MODEL};
        const cuuint64_t gstride[1] = {(cuuint64_t)(NH * DH * 2)};
        const cuuint32_t box[2] = {(cuuint32_t)DH, (cuuint32_t)QROWS};
        const cuuint32_t estride[2] = {1, 1};
        ((encode_fn)fn)(&tm_wq, CU_TENSOR_MAP_DATA_TYPE_BFLOAT16, 2, d_in[3], gdim, gstride, box, estride,
                        CU_TENSOR_MAP_INTERLEAVE_NONE, CU_TENSOR_MAP_SWIZZLE_NONE, CU_TENSOR_MAP_L2_PROMOTION_NONE,
                        CU_TENSOR_MAP_FLOAT_OOB_FILL_NONE);
        cudaFuncSetAttribute(fused_decode_kernel, cudaFuncAttributeMaxDynamicSharedMemorySize, SM_TOTAL);
        tm_ptr = d_in[3];
    }
    fused_decode_kernel<<<NCTA, NTHREADS, SM_TOTAL, cudaStreamPerThread>>>(tm_wq, x, kc, vc, wo, w1, b1, w2, b2,
                                                                          (__nv_bfloat16*)d_out);
}
```

```cpp
#include <cuda_runtime.h>
#include <cuda.h>
#include <cuda_bf16.h>
#include <stdint.h>

namespace {

constexpr int D_MODEL = 640;
constexpr int NH = 32;
constexpr int SK = 32768;
constexpr int DH = 128;
constexpr int FF = 1728;

constexpr int SPLITS = 4;
constexpr int NCTA = NH * SPLITS;
constexpr int TILE_KEYS = 128;
constexpr int STAGE_BYTES = TILE_KEYS * DH * 2;
constexpr int NTILES = SK / SPLITS / TILE_KEYS;
constexpr int NITEMS = 2 * NTILES;
constexpr int NSTAGE = 6;

constexpr int FILL_WINDOW = 4;

constexpr int QROWS = D_MODEL / SPLITS;
constexpr int WO_ROWS = DH / SPLITS;
constexpr int WO_ROW_BYTES = D_MODEL * 2;
constexpr int WO_BLOCKS = D_MODEL / 64;
constexpr int NFIN = D_MODEL / 8;

constexpr int NCW = 8;
constexpr int NTHREADS = 32 * (NCW + 2);

constexpr int W_STAGE = NSTAGE - 1;
constexpr int SM_W = W_STAGE * STAGE_BYTES;
constexpr int W_BYTES = WO_ROWS * WO_ROW_BYTES;
constexpr int SM_RED = SM_W + W_BYTES;
constexpr int SM_ML = SM_RED + NCW * DH * 4;
constexpr int SM_QS = SM_ML + NCW * 8;
constexpr int SM_OB = SM_QS + DH * 2;
constexpr int SM_FIN = SM_OB + WO_ROWS * 2;
constexpr int SM_MLP = SM_FIN + NCW * 8 * 4;
constexpr int SM_MW = SM_MLP + 8 * 4;
constexpr int SM_BAR = SM_MW + 3 * FF * 2;
constexpr int SM_TOTAL = SM_BAR + (2 * NSTAGE + 4) * 8;
static_assert(SM_MW % 16 == 0 && SM_BAR % 8 == 0 && SM_RED % 16 == 0, "alignment");
static_assert(W_BYTES >= STAGE_BYTES && W_BYTES >= QROWS * DH * 2, "weight buffer");
constexpr int LAST_W = ((NITEMS - 1 - W_STAGE) / NSTAGE) * NSTAGE + W_STAGE;
static_assert(LAST_W < NITEMS - 2, "wo must not wait for the last tile");

constexpr float LOG2E = 1.4426950408889634f;
constexpr float SM_SCALE = 0.08838834764831845f;
constexpr float LN_EPS = 1e-5f;
constexpr uint32_t SPIN_LIMIT = 1u << 24;

struct Scratch {
    unsigned long long qx[NH][SPLITS][DH];
    unsigned long long ox[NH][SPLITS][DH + 8];
    unsigned long long tx[NFIN][NCTA][8];
    unsigned int epoch;
};
__device__ __align__(128) Scratch g_scr;

__device__ __forceinline__ uint32_t smem_u32(const void* p) { return (uint32_t)__cvta_generic_to_shared(p); }

__device__ __forceinline__ void mbar_init(uint32_t bar, uint32_t cnt) {
    asm volatile("mbarrier.init.shared::cta.b64 [%0], %1;" ::"r"(bar), "r"(cnt) : "memory");
}
__device__ __forceinline__ void mbar_expect_tx(uint32_t bar, uint32_t bytes) {
    asm volatile("mbarrier.arrive.expect_tx.shared::cta.b64 _, [%0], %1;" ::"r"(bar), "r"(bytes) : "memory");
}
__device__ __forceinline__ void mbar_arrive(uint32_t bar) {
    asm volatile("mbarrier.arrive.shared::cta.b64 _, [%0];" ::"r"(bar) : "memory");
}
__device__ __forceinline__ void mbar_wait(uint32_t bar, uint32_t parity) {
    uint32_t done, it = 0;
    do {
        asm volatile(
            "{\n.reg .pred p;\n"
            "mbarrier.try_wait.parity.shared::cta.b64 p, [%1], %2;\n"
            "selp.u32 %0, 1, 0, p;\n}"
            : "=r"(done) : "r"(bar), "r"(parity) : "memory");
        if (++it > SPIN_LIMIT) __trap();
    } while (!done);
}
__device__ __forceinline__ void bulk_load(uint32_t dst, const void* src, uint32_t bytes, uint32_t bar) {
    asm volatile("cp.async.bulk.shared::cluster.global.mbarrier::complete_tx::bytes [%0], [%1], %2, [%3];"
                 ::"r"(dst), "l"(src), "r"(bytes), "r"(bar) : "memory");
}
__device__ __forceinline__ void bulk_load_stream(uint32_t dst, const void* src, uint32_t bytes, uint32_t bar, uint64_t pol) {
    asm volatile("cp.async.bulk.shared::cluster.global.mbarrier::complete_tx::bytes.L2::cache_hint [%0], [%1], %2, [%3], %4;"
                 ::"r"(dst), "l"(src), "r"(bytes), "r"(bar), "l"(pol) : "memory");
}
__device__ __forceinline__ const uint8_t* item_src(int i, const uint8_t* kbase, const uint8_t* vbase) {
    const bool is_k = (i == 0) || ((i & 1) && i != NITEMS - 1);
    const int tile = is_k ? (i + 1) >> 1 : (i == NITEMS - 1 ? NTILES - 1 : (i >> 1) - 1);
    return (is_k ? kbase : vbase) + (size_t)tile * (SPLITS * STAGE_BYTES);
}
__device__ __forceinline__ void ldsm_x4(uint32_t (&r)[4], uint32_t addr) {
    asm volatile("ldmatrix.sync.aligned.m8n8.x4.shared.b16 {%0,%1,%2,%3}, [%4];"
                 : "=r"(r[0]), "=r"(r[1]), "=r"(r[2]), "=r"(r[3]) : "r"(addr) : "memory");
}
__device__ __forceinline__ void ldsm_x4_t(uint32_t (&r)[4], uint32_t addr) {
    asm volatile("ldmatrix.sync.aligned.m8n8.x4.trans.shared.b16 {%0,%1,%2,%3}, [%4];"
                 : "=r"(r[0]), "=r"(r[1]), "=r"(r[2]), "=r"(r[3]) : "r"(addr) : "memory");
}
__device__ __forceinline__ void mma_bf16(float (&d)[4], const uint32_t (&a)[4], uint32_t b0, uint32_t b1) {
    asm volatile("mma.sync.aligned.m16n8k16.row.col.f32.bf16.bf16.f32 {%0,%1,%2,%3}, {%4,%5,%6,%7}, {%8,%9}, {%0,%1,%2,%3};"
                 : "+f"(d[0]), "+f"(d[1]), "+f"(d[2]), "+f"(d[3])
                 : "r"(a[0]), "r"(a[1]), "r"(a[2]), "r"(a[3]), "r"(b0), "r"(b1));
}
__device__ __forceinline__ float ex2(float x) {
    float y;
    asm("ex2.approx.ftz.f32 %0, %1;" : "=f"(y) : "f"(x));
    return y;
}
__device__ __forceinline__ float bf16r(float x) { return __bfloat162float(__float2bfloat16_rn(x)); }
__device__ __forceinline__ float bf_lo(uint32_t u) { return __uint_as_float(u << 16); }
__device__ __forceinline__ float bf_hi(uint32_t u) { return __uint_as_float(u & 0xffff0000u); }
__device__ __forceinline__ uint32_t pack_bf16(float lo, float hi) {
    uint32_t r;
    asm("cvt.rn.bf16x2.f32 %0, %1, %2;" : "=r"(r) : "f"(hi), "f"(lo));
    return r;
}
__device__ __forceinline__ void named_sync(int id, int n) { asm volatile("bar.sync %0, %1;" ::"r"(id), "r"(n) : "memory"); }
__device__ __forceinline__ void named_arrive(int id, int n) { asm volatile("bar.arrive %0, %1;" ::"r"(id), "r"(n) : "memory"); }

__device__ __forceinline__ void ll_store(unsigned long long* p, float v, uint32_t tag) {
    unsigned long long w = ((unsigned long long)tag << 32) | (unsigned long long)__float_as_uint(v);
    asm volatile("st.relaxed.gpu.global.b64 [%0], %1;" ::"l"(p), "l"(w) : "memory");
}
__device__ __forceinline__ unsigned long long ll_load(const unsigned long long* p) {
    unsigned long long w;
    asm volatile("ld.relaxed.gpu.global.b64 %0, [%1];" : "=l"(w) : "l"(p) : "memory");
    return w;
}
__device__ __forceinline__ void ll_load2(const unsigned long long* p, unsigned long long& a, unsigned long long& b) {
    asm volatile("ld.relaxed.gpu.global.v2.b64 {%0,%1}, [%2];" : "=l"(a), "=l"(b) : "l"(p) : "memory");
}
__device__ __forceinline__ bool ll_ok(unsigned long long w, uint32_t tag) { return (uint32_t)(w >> 32) == tag; }
__device__ __forceinline__ float ll_val(unsigned long long w) { return __uint_as_float((uint32_t)w); }

__device__ __forceinline__ float warp_sum(float v) {
#pragma unroll
    for (int o = 16; o > 0; o >>= 1) v += __shfl_xor_sync(0xffffffffu, v, o);
    return v;
}
__device__ __forceinline__ float warp_max(float v) {
#pragma unroll
    for (int o = 16; o > 0; o >>= 1) v = fmaxf(v, __shfl_xor_sync(0xffffffffu, v, o));
    return v;
}
__device__ __forceinline__ uint2 ldg_u64(const void* p) {
    uint2 v;
    asm volatile("ld.global.nc.v2.u32 {%0,%1}, [%2];" : "=r"(v.x), "=r"(v.y) : "l"(p));
    return v;
}
__device__ __forceinline__ uint32_t ldg_u16(const void* p) {
    uint16_t v;
    asm volatile("ld.global.nc.u16 %0, [%1];" : "=h"(v) : "l"(p));
    return v;
}
__device__ __forceinline__ void unpack_x20(const uint2 (&u)[5], float (&v)[20]) {
#pragma unroll
    for (int i = 0; i < 5; i++) {
        v[4 * i + 0] = bf_lo(u[i].x); v[4 * i + 1] = bf_hi(u[i].x);
        v[4 * i + 2] = bf_lo(u[i].y); v[4 * i + 3] = bf_hi(u[i].y);
    }
}

__device__ __forceinline__ void ln_stats(const float (&v)[20], float& mean_b, float& den_b) {
    float s = 0.f;
#pragma unroll
    for (int i = 0; i < 20; i++) s += v[i];
    const float mean = warp_sum(s) * (1.0f / D_MODEL);
    float q = 0.f;
#pragma unroll
    for (int i = 0; i < 20; i++) { const float d = v[i] - mean; q = fmaf(d, d, q); }
    const float var = warp_sum(q) * (1.0f / D_MODEL);
    mean_b = bf16r(mean);
    den_b = bf16r(sqrtf(bf16r(bf16r(var) + LN_EPS)));
}
__device__ __forceinline__ float ln_apply(float x, float mean_b, float den_b) {
    return bf16r(__fdiv_rn(bf16r(x - mean_b), den_b));
}

__global__ void __launch_bounds__(NTHREADS, 1)
fused_decode_kernel(const __grid_constant__ CUtensorMap tm_wq, const __grid_constant__ CUtensorMap tm_wo,
                    const __nv_bfloat16* __restrict__ x, const __nv_bfloat16* __restrict__ kc,
                    const __nv_bfloat16* __restrict__ vc,
                    const __nv_bfloat16* __restrict__ w1, const __nv_bfloat16* __restrict__ b1,
                    const __nv_bfloat16* __restrict__ w2, const __nv_bfloat16* __restrict__ b2,
                    __nv_bfloat16* __restrict__ out)
{
    extern __shared__ __align__(1024) uint8_t smem[];
    const uint32_t sbase = smem_u32(smem);
    const int tid = threadIdx.x, warp = tid >> 5, lane = tid & 31;
    const int cta = blockIdx.x, head = cta / SPLITS, split = cta % SPLITS;
    const uint32_t bar_full = sbase + SM_BAR, bar_empty = bar_full + NSTAGE * 8, bar_w = bar_empty + NSTAGE * 8,
                   bar_m = bar_w + 8, bar_q = bar_m + 8, bar_qd = bar_q + 8;

    const size_t kv_off = ((size_t)head * SK + (size_t)split * TILE_KEYS) * (DH * 2);
    const uint8_t* kbase = reinterpret_cast<const uint8_t*>(kc) + kv_off;
    const uint8_t* vbase = reinterpret_cast<const uint8_t*>(vc) + kv_off;
    uint64_t pol = 0;

    uint2 xraw[5];
    uint32_t xrow[10];
    uint32_t epoch = 0, xfin = 0;
    if (warp == 0) {
        if (lane == 0) {
            asm volatile("prefetch.tensormap [%0];" ::"l"(&tm_wq) : "memory");
            mbar_init(bar_q, 1);
            asm volatile("fence.proxy.async.shared::cta;" ::: "memory");
            mbar_expect_tx(bar_q, QROWS * DH * 2);
            asm volatile("cp.async.bulk.tensor.2d.shared::cluster.global.mbarrier::complete_tx::bytes [%0], [%1, {%3, %4}], [%2];"
                         ::"r"(sbase + SM_W), "l"(&tm_wq), "r"(bar_q), "r"(head * DH), "r"(split * QROWS) : "memory");
            for (int s = 0; s < NSTAGE; s++) {
                mbar_init(bar_full + s * 8, 1);
                mbar_init(bar_empty + s * 8, NCW);
            }
            mbar_init(bar_w, 1);
            mbar_init(bar_m, 1);
            mbar_init(bar_qd, NCW);
            asm volatile("fence.proxy.async.shared::cta;" ::: "memory");
            asm volatile("createpolicy.fractional.L2::evict_first.b64 %0, 1.0;" : "=l"(pol));
            for (int i = 0; i < FILL_WINDOW; i++) {
                mbar_expect_tx(bar_full + i * 8, STAGE_BYTES);
                bulk_load_stream(sbase + i * STAGE_BYTES, item_src(i, kbase, vbase), STAGE_BYTES, bar_full + i * 8, pol);
            }
        }
        __syncwarp();
        asm volatile("ld.volatile.global.u32 %0, [%1];" : "=r"(epoch) : "l"(&g_scr.epoch) : "memory");
    } else {
        if (warp <= NCW) {
            const int ct = tid - 32;
            asm volatile("ld.volatile.global.u32 %0, [%1];" : "=r"(epoch) : "l"(&g_scr.epoch) : "memory");
#pragma unroll
            for (int i = 0; i < 10; i++) xrow[i] = ldg_u16(x + split * QROWS + (ct >> 4) + 16 * i);
            xfin = ldg_u16(x + (cta < NFIN ? cta * 8 : 0) + (ct & 7));
        }
#pragma unroll
        for (int i = 0; i < 5; i++) xraw[i] = ldg_u64(reinterpret_cast<const uint2*>(x) + lane + 32 * i);
        if (warp <= NCW) {
            const int ct = tid - 32;
            if (ct < DH) ll_store(&g_scr.qx[head][split][ct], 0.f, 0u);
            if (ct < DH + 8) ll_store(&g_scr.ox[head][split][ct], 0.f, 0u);
#pragma unroll
            for (int k = 0; k < 3; k++) {
                const int idx = ct + 256 * k;
                if (idx < D_MODEL) ll_store(&g_scr.tx[idx >> 3][cta][idx & 7], 0.f, 0u);
            }
        }
    }
    __syncthreads();

    if (warp == 0) {
        if (lane == 0) {
            for (int i = FILL_WINDOW; i < NSTAGE; i++) {
                mbar_wait(bar_full + (i - FILL_WINDOW) * 8, 0);
                if (i == W_STAGE) mbar_wait(bar_qd, 0);
                mbar_expect_tx(bar_full + i * 8, STAGE_BYTES);
                bulk_load_stream(sbase + i * STAGE_BYTES, item_src(i, kbase, vbase), STAGE_BYTES, bar_full + i * 8, pol);
            }
            if (cta < NFIN) {
                mbar_expect_tx(bar_m, 3 * FF * 2);
                bulk_load(sbase + SM_MW, w1, FF * 2, bar_m);
                bulk_load(sbase + SM_MW + FF * 2, b1, FF * 2, bar_m);
                bulk_load(sbase + SM_MW + 2 * FF * 2, w2, FF * 2, bar_m);
            }
            asm volatile("prefetch.tensormap [%0];" ::"l"(&tm_wo) : "memory");
            int slot = 0;
            uint32_t ph = 0;
            for (int i = NSTAGE; i < NITEMS; i++) {
                mbar_wait(bar_empty + slot * 8, ph);
                mbar_expect_tx(bar_full + slot * 8, STAGE_BYTES);
                bulk_load_stream(sbase + slot * STAGE_BYTES, item_src(i, kbase, vbase), STAGE_BYTES, bar_full + slot * 8, pol);
                if (++slot == NSTAGE) { slot = 0; ph ^= 1; }
            }
            mbar_wait(bar_empty + W_STAGE * 8, (LAST_W / NSTAGE) & 1);
            mbar_expect_tx(bar_w, W_BYTES);
            asm volatile("cp.async.bulk.tensor.3d.shared::cluster.global.mbarrier::complete_tx::bytes [%0], [%1, {%3, %4, %3}], [%2];"
                         ::"r"(sbase + SM_W), "l"(&tm_wo), "r"(bar_w), "r"(0), "r"(head * DH + split * WO_ROWS) : "memory");
        }
        __syncwarp();

        {
            const uint32_t tag = epoch + 1u;
            unsigned long long wo4[SPLITS], wm[SPLITS], wl[SPLITS];
            uint32_t it = 0;
            bool ok;
            do {
                ok = true;
#pragma unroll
                for (int i = 0; i < SPLITS; i++) {
                    wo4[i] = ll_load(&g_scr.ox[head][i][split * WO_ROWS + lane]);
                    ll_load2(&g_scr.ox[head][i][DH], wm[i], wl[i]);
                }
#pragma unroll
                for (int i = 0; i < SPLITS; i++) ok = ok && ll_ok(wo4[i], tag) && ll_ok(wm[i], tag) && ll_ok(wl[i], tag);
                if (++it > SPIN_LIMIT) __trap();
            } while (!ok);
            float M = ll_val(wm[0]);
#pragma unroll
            for (int i = 1; i < SPLITS; i++) M = fmaxf(M, ll_val(wm[i]));
            float o = 0.f, L = 0.f;
#pragma unroll
            for (int i = 0; i < SPLITS; i++) {
                const float e = ex2((ll_val(wm[i]) - M) * LOG2E);
                o = fmaf(e, ll_val(wo4[i]), o);
                L = fmaf(e, ll_val(wl[i]), L);
            }
            reinterpret_cast<__nv_bfloat16*>(smem + SM_OB)[lane] = __float2bfloat16_rn(__fdiv_rn(o, L));
            __syncwarp();
            named_arrive(3, NCW * 32 + 32);
        }
    } else if (warp <= NCW) {
        const int cw = warp - 1, ct = tid - 32;
        const int g = lane >> 2, t = lane & 3;
        float* red = reinterpret_cast<float*>(smem + SM_RED);
        const uint32_t tag = epoch + 1u;

        {
            float xv[20];
            unpack_x20(xraw, xv);
            float mean_b, den_b;
            ln_stats(xv, mean_b, den_b);
            float a[8];
#pragma unroll
            for (int j = 0; j < 8; j++) a[j] = 0.f;
            float xn[10];
#pragma unroll
            for (int i = 0; i < 10; i++) xn[i] = ln_apply(bf_lo(xrow[i]), mean_b, den_b);
            mbar_wait(bar_q, 0);
            const uint4* wsm = reinterpret_cast<const uint4*>(smem + SM_W) + ct;
#pragma unroll
            for (int i = 0; i < 10; i++) {
                const uint4 w = wsm[i * 256];
                a[0] = fmaf(xn[i], bf_lo(w.x), a[0]); a[1] = fmaf(xn[i], bf_hi(w.x), a[1]);
                a[2] = fmaf(xn[i], bf_lo(w.y), a[2]); a[3] = fmaf(xn[i], bf_hi(w.y), a[3]);
                a[4] = fmaf(xn[i], bf_lo(w.z), a[4]); a[5] = fmaf(xn[i], bf_hi(w.z), a[5]);
                a[6] = fmaf(xn[i], bf_lo(w.w), a[6]); a[7] = fmaf(xn[i], bf_hi(w.w), a[7]);
            }
            __syncwarp();
            if (lane == 0) mbar_arrive(bar_qd);
#pragma unroll
            for (int j = 0; j < 8; j++) a[j] += __shfl_xor_sync(0xffffffffu, a[j], 16);
            if (lane < 16) {
                float4* dst = reinterpret_cast<float4*>(red + cw * DH + lane * 8);
                dst[0] = make_float4(a[0], a[1], a[2], a[3]);
                dst[1] = make_float4(a[4], a[5], a[6], a[7]);
            }
            named_sync(1, NCW * 32);
            if (ct < DH) {
                float s = 0.f;
#pragma unroll
                for (int w = 0; w < NCW; w++) s += red[w * DH + ct];
                ll_store(&g_scr.qx[head][split][ct], s, tag);
                unsigned long long w4[SPLITS];
                uint32_t it = 0;
                bool ok;
                do {
#pragma unroll
                    for (int i = 0; i < SPLITS; i++) w4[i] = ll_load(&g_scr.qx[head][i][ct]);
                    ok = true;
#pragma unroll
                    for (int i = 0; i < SPLITS; i++) ok = ok && ll_ok(w4[i], tag);
                    if (++it > SPIN_LIMIT) __trap();
                } while (!ok);
                const float q = (ll_val(w4[0]) + ll_val(w4[1])) + (ll_val(w4[2]) + ll_val(w4[3]));
                reinterpret_cast<__nv_bfloat16*>(smem + SM_QS)[ct] = __float2bfloat16_rn(q);
            }
            named_sync(1, NCW * 32);
        }

        uint32_t qf[8][2];
#pragma unroll
        for (int s = 0; s < 8; s++) {
            const uint32_t* qs = reinterpret_cast<const uint32_t*>(smem + SM_QS);
            qf[s][0] = qs[4 * (s ^ g) + t];
            qf[s][1] = qs[32 + 4 * (s ^ g) + t];
        }

        float acc[8][4];
#pragma unroll
        for (int c = 0; c < 8; c++) { acc[c][0] = acc[c][1] = acc[c][2] = acc[c][3] = 0.f; }
        float m_run = -INFINITY, l_run = 0.f;
        const bool valid = (t == (g >> 1));
        const bool odd = g & 1;
        const uint32_t sel0 = odd ? 0x1044u : 0x4410u;
        const uint32_t sel1 = odd ? 0x3244u : 0x4432u;
        const int mi = lane >> 3, rho = lane & 7;
        const uint32_t k_off = (uint32_t)(cw * 16 + rho + 8 * (mi & 1)) * 256u + (uint32_t)(mi >> 1) * 128u + (uint32_t)rho * 16u;
        const uint32_t v_off = (uint32_t)(cw * 16 + rho + 8 * (mi >> 1)) * 256u + (uint32_t)(mi & 1) * 128u + (uint32_t)rho * 16u;

        int slot = 0;
        uint32_t ph = 0;
        auto qk_tile = [&](float& sa, float& sb) {
            const uint32_t ka = sbase + slot * STAGE_BYTES + k_off;
            mbar_wait(bar_full + slot * 8, ph);
            float s0[4] = {0.f, 0.f, 0.f, 0.f}, s1[4] = {0.f, 0.f, 0.f, 0.f};
#pragma unroll
            for (int s = 0; s < 8; s += 2) {
                uint32_t r[4], u[4];
                ldsm_x4(r, ka ^ (uint32_t)(s << 4));
                ldsm_x4(u, ka ^ (uint32_t)((s + 1) << 4));
                mma_bf16(s0, r, qf[s][0], qf[s][1]);
                mma_bf16(s1, u, qf[s + 1][0], qf[s + 1][1]);
            }
            __syncwarp();
            if (lane == 0) mbar_arrive(bar_empty + slot * 8);
            if (++slot == NSTAGE) { slot = 0; ph ^= 1; }
            const float ra = odd ? (s0[1] + s1[1]) : (s0[0] + s1[0]);
            const float rb = odd ? (s0[3] + s1[3]) : (s0[2] + s1[2]);
            sa = valid ? bf16r(bf16r(ra) * SM_SCALE) : -INFINITY;
            sb = valid ? bf16r(bf16r(rb) * SM_SCALE) : -INFINITY;
        };
        auto raise_max = [&](float m_new) {
            const float sc = ex2((m_run - m_new) * LOG2E);
#pragma unroll
            for (int c = 0; c < 8; c++) { acc[c][0] *= sc; acc[c][1] *= sc; acc[c][2] *= sc; acc[c][3] *= sc; }
            l_run *= sc;
            m_run = m_new;
        };
        auto probs = [&](float sa, float sb, uint32_t& b0, uint32_t& b1) {
            const float pa = ex2((sa - m_run) * LOG2E);
            const float pb = ex2((sb - m_run) * LOG2E);
            l_run += pa + pb;
            const uint32_t pk = pack_bf16(pa, pb);
            b0 = __byte_perm(pk, 0u, sel0);
            b1 = __byte_perm(pk, 0u, sel1);
        };
        auto pv_tile = [&](uint32_t b0, uint32_t b1) {
            const uint32_t va = sbase + slot * STAGE_BYTES + v_off;
            mbar_wait(bar_full + slot * 8, ph);
#pragma unroll
            for (int c = 0; c < 8; c++) {
                uint32_t r[4];
                ldsm_x4_t(r, va ^ (uint32_t)(c << 4));
                mma_bf16(acc[c], r, b0, b1);
            }
            __syncwarp();
            if (lane == 0) mbar_arrive(bar_empty + slot * 8);
            if (++slot == NSTAGE) { slot = 0; ph ^= 1; }
        };

        float ca, cb;
        qk_tile(ca, cb);
        m_run = warp_max(fmaxf(ca, cb));
#pragma unroll 1
        for (int tile = 0; tile < NTILES - 2; tile++) {
            float na, nb;
            qk_tile(na, nb);
            const float smax = fmaxf(na, nb);
            if (__any_sync(0xffffffffu, smax > m_run)) raise_max(warp_max(smax));
            uint32_t b0, b1;
            probs(ca, cb, b0, b1);
            pv_tile(b0, b1);
            ca = na; cb = nb;
        }
        {
            float na, nb;
            qk_tile(na, nb);
            float* mw = reinterpret_cast<float*>(smem + SM_ML);
            const float m_new = fmaxf(m_run, warp_max(fmaxf(na, nb)));
            if (lane == 0) mw[cw] = m_new;
            named_sync(1, NCW * 32);
            const float4 ma = *reinterpret_cast<const float4*>(mw), mb = *reinterpret_cast<const float4*>(mw + 4);
            raise_max(fmaxf(fmaxf(fmaxf(ma.x, ma.y), fmaxf(ma.z, ma.w)), fmaxf(fmaxf(mb.x, mb.y), fmaxf(mb.z, mb.w))));
            uint32_t b0, b1, c0, c1;
            probs(ca, cb, b0, b1);
            probs(na, nb, c0, c1);
            const float lw = warp_sum(l_run);
            if (lane == 0) mw[NCW + cw] = lw;
            pv_tile(b0, b1);
            pv_tile(c0, c1);
        }

        {
            float u[2][8];
#pragma unroll
            for (int c = 0; c < 8; c++) {
                u[0][c] = acc[c][0] + acc[c ^ 1][1];
                u[1][c] = acc[c][2] + acc[c ^ 1][3];
            }
#pragma unroll
            for (int hf = 0; hf < 2; hf++) {
#pragma unroll
                for (int c = 0; c < 8; c++)
                    if (!(c & 2)) u[hf][c] += __shfl_xor_sync(0xffffffffu, u[hf][c ^ 2], 1);
                u[hf][0] += __shfl_xor_sync(0xffffffffu, u[hf][4], 2);
                u[hf][1] += __shfl_xor_sync(0xffffffffu, u[hf][5], 2);
                red[cw * DH + 64 * hf + 16 * t + g] = u[hf][0];
                red[cw * DH + 64 * hf + 16 * t + 8 + g] = u[hf][1];
            }
        }
        named_sync(1, NCW * 32);

        if (ct < DH) {
            const float o = ((red[ct] + red[DH + ct]) + (red[2 * DH + ct] + red[3 * DH + ct])) +
                            ((red[4 * DH + ct] + red[5 * DH + ct]) + (red[6 * DH + ct] + red[7 * DH + ct]));
            ll_store(&g_scr.ox[head][split][ct], o, tag);
        } else if (ct == DH) {
            const float4 la = *reinterpret_cast<const float4*>(smem + SM_ML + NCW * 4);
            const float4 lb = *reinterpret_cast<const float4*>(smem + SM_ML + NCW * 4 + 16);
            ll_store(&g_scr.ox[head][split][DH], m_run, tag);
            ll_store(&g_scr.ox[head][split][DH + 1], ((la.x + la.y) + (la.z + la.w)) + ((lb.x + lb.y) + (lb.z + lb.w)), tag);
        }

        unsigned long long* txp = &g_scr.tx[cw * 10 + (t & 1) + 2 * (t >> 1)][cta][g];
        uint32_t wa[5];
#pragma unroll
        for (int i = 0; i < 5; i++) {
            const int col = cw * 80 + 16 * i + 8 * (mi & 1), row = rho + 8 * (mi >> 1);
            wa[i] = sbase + SM_W + (uint32_t)(col >> 6) * (WO_ROWS * 128) + (uint32_t)row * 128u + (uint32_t)((((col >> 3) & 7) ^ rho) << 4);
        }
        mbar_wait(bar_w, 0);
        uint32_t wf[5][2][4];
#pragma unroll
        for (int i = 0; i < 5; i++) {
            ldsm_x4_t(wf[i][0], wa[i]);
            ldsm_x4_t(wf[i][1], wa[i] + 16 * 128);
        }
        named_sync(3, NCW * 32 + 32);

        {
            const uint32_t* ob = reinterpret_cast<const uint32_t*>(smem + SM_OB);
            const uint32_t b00 = ob[t], b01 = ob[4 + t], b10 = ob[8 + t], b11 = ob[12 + t];
            float d[5][4];
#pragma unroll
            for (int i = 0; i < 5; i++) {
                d[i][0] = d[i][1] = d[i][2] = d[i][3] = 0.f;
                mma_bf16(d[i], wf[i][0], b00, b01);
                mma_bf16(d[i], wf[i][1], b10, b11);
            }
#pragma unroll
            for (int k = 0; k < 3; k++) {
                const int i0 = 2 * k, i1 = (2 * k + 1 < 5) ? 2 * k + 1 : 2 * k;
                const float v0 = (t & 1) ? d[i0][2] : d[i0][0];
                const float v1 = (t & 1) ? d[i1][2] : d[i1][0];
                const float v = (t >> 1) ? v1 : v0;
                if (k < 2 || t < 2) ll_store(txp + (size_t)(4 * k) * NCTA * 8, v, tag);
            }
        }

        if (cta < NFIN) {
            const unsigned long long* src = &g_scr.tx[cta][ct >> 1][(ct & 1) * 4];
            unsigned long long w0, w1_, w2_, w3;
            uint32_t it = 0;
            bool ok;
            do {
                ll_load2(src, w0, w1_);
                ll_load2(src + 2, w2_, w3);
                ok = ll_ok(w0, tag) && ll_ok(w1_, tag) && ll_ok(w2_, tag) && ll_ok(w3, tag);
                if (++it > SPIN_LIMIT) __trap();
            } while (!ok);
            float v0 = ll_val(w0), v1 = ll_val(w1_), v2 = ll_val(w2_), v3 = ll_val(w3);
            const bool b1 = lane & 2, b2 = lane & 4;
            float k0 = b1 ? v2 : v0, k1 = b1 ? v3 : v1;
            k0 += __shfl_xor_sync(0xffffffffu, b1 ? v0 : v2, 2);
            k1 += __shfl_xor_sync(0xffffffffu, b1 ? v1 : v3, 2);
            float k = b2 ? k1 : k0;
            k += __shfl_xor_sync(0xffffffffu, b2 ? k0 : k1, 4);
            k += __shfl_xor_sync(0xffffffffu, k, 8);
            k += __shfl_xor_sync(0xffffffffu, k, 16);
            if (lane < 8)
                reinterpret_cast<float*>(smem + SM_FIN)[cw * 8 + 4 * (lane & 1) + (lane & 2) + (lane >> 2)] = k;
            named_sync(2, NCW * 32 + 32);
            if (ct < 8) {
                const float* fin = reinterpret_cast<const float*>(smem + SM_FIN);
                const float a = ((fin[ct] + fin[8 + ct]) + (fin[16 + ct] + fin[24 + ct])) +
                                ((fin[32 + ct] + fin[40 + ct]) + (fin[48 + ct] + fin[56 + ct]));
                const float r = bf16r(bf_lo(xfin) + bf16r(a));
                out[cta * 8 + ct] = __float2bfloat16_rn(r + reinterpret_cast<const float*>(smem + SM_MLP)[ct]);
                if (cta == 0 && ct == 0) *reinterpret_cast<volatile unsigned int*>(&g_scr.epoch) = tag;
            }
        }
    } else if (cta < NFIN) {
        float xv[20];
        unpack_x20(xraw, xv);
        float mean_b, den_b;
        ln_stats(xv, mean_b, den_b);
#pragma unroll
        for (int i = 0; i < 20; i++) xv[i] = ln_apply(xv[i], mean_b, den_b);
        float mean2, den2;
        ln_stats(xv, mean2, den2);
        float h[8], y[8];
#pragma unroll
        for (int j = 0; j < 8; j++) {
            const float xn = ln_apply(__bfloat162float(x[cta * 8 + j]), mean_b, den_b);
            h[j] = ln_apply(xn, mean2, den2);
            y[j] = 0.f;
        }
        const __nv_bfloat16* mw = reinterpret_cast<const __nv_bfloat16*>(smem + SM_MW);
        mbar_wait(bar_m, 0);
        for (int f = lane; f < FF; f += 32) {
            const float a = __bfloat162float(mw[f]), b = __bfloat162float(mw[FF + f]), c = __bfloat162float(mw[2 * FF + f]);
#pragma unroll
            for (int j = 0; j < 8; j++) {
                const float u = bf16r(bf16r(h[j] * a) + b);
                const float inner = 0.7978845608028654f * (u + 0.044715f * u * u * u);
                const float gl = bf16r(0.5f * u * (1.0f + tanhf(inner)));
                y[j] = fmaf(gl, c, y[j]);
            }
        }
        const float bias2 = __bfloat162float(b2[0]);
#pragma unroll
        for (int j = 0; j < 8; j++) {
            const float s = warp_sum(y[j]);
            if (lane == j) reinterpret_cast<float*>(smem + SM_MLP)[j] = bf16r(bf16r(s) + bias2);
        }
        __syncwarp();
        named_arrive(2, NCW * 32 + 32);
    }
}

}

extern "C" void kernel_launch(void* const* d_in, const int* in_sizes, int n_in, void* d_out, int out_size) {
    (void)in_sizes; (void)n_in; (void)out_size;
    const __nv_bfloat16* x = (const __nv_bfloat16*)d_in[0];
    const __nv_bfloat16* kc = (const __nv_bfloat16*)d_in[1];
    const __nv_bfloat16* vc = (const __nv_bfloat16*)d_in[2];
    const __nv_bfloat16* w1 = (const __nv_bfloat16*)d_in[6];
    const __nv_bfloat16* b1 = (const __nv_bfloat16*)d_in[7];
    const __nv_bfloat16* w2 = (const __nv_bfloat16*)d_in[8];
    const __nv_bfloat16* b2 = (const __nv_bfloat16*)d_in[9];

    static CUtensorMap tm_wq, tm_wo;
    static void *wq_ptr = nullptr, *wo_ptr = nullptr;
    if (wq_ptr != d_in[3] || wo_ptr != d_in[4]) {
        typedef CUresult (*encode_fn)(CUtensorMap*, CUtensorMapDataType, cuuint32_t, void*, const cuuint64_t*,
                                      const cuuint64_t*, const cuuint32_t*, const cuuint32_t*, CUtensorMapInterleave,
                                      CUtensorMapSwizzle, CUtensorMapL2promotion, CUtensorMapFloatOOBfill);
        void* fn = nullptr;
        cudaDriverEntryPointQueryResult qr;
        cudaGetDriverEntryPoint("cuTensorMapEncodeTiled", &fn, cudaEnableDefault, &qr);
        const cuuint64_t gdim[2] = {(cuuint64_t)(NH * DH), (cuuint64_t)D_MODEL};
        const cuuint64_t gstride[1] = {(cuuint64_t)(NH * DH * 2)};
        const cuuint32_t box[2] = {(cuuint32_t)DH, (cuuint32_t)QROWS};
        const cuuint32_t estride[2] = {1, 1};
        ((encode_fn)fn)(&tm_wq, CU_TENSOR_MAP_DATA_TYPE_BFLOAT16, 2, d_in[3], gdim, gstride, box, estride,
                        CU_TENSOR_MAP_INTERLEAVE_NONE, CU_TENSOR_MAP_SWIZZLE_NONE, CU_TENSOR_MAP_L2_PROMOTION_NONE,
                        CU_TENSOR_MAP_FLOAT_OOB_FILL_NONE);
        const cuuint64_t odim[3] = {64, (cuuint64_t)(NH * DH), (cuuint64_t)WO_BLOCKS};
        const cuuint64_t ostride[2] = {(cuuint64_t)WO_ROW_BYTES, 128};
        const cuuint32_t obox[3] = {64, (cuuint32_t)WO_ROWS, (cuuint32_t)WO_BLOCKS};
        const cuuint32_t oestride[3] = {1, 1, 1};
        ((encode_fn)fn)(&tm_wo, CU_TENSOR_MAP_DATA_TYPE_BFLOAT16, 3, d_in[4], odim, ostride, obox, oestride,
                        CU_TENSOR_MAP_INTERLEAVE_NONE, CU_TENSOR_MAP_SWIZZLE_128B, CU_TENSOR_MAP_L2_PROMOTION_NONE,
                        CU_TENSOR_MAP_FLOAT_OOB_FILL_NONE);
        cudaFuncSetAttribute(fused_decode_kernel, cudaFuncAttributeMaxDynamicSharedMemorySize, SM_TOTAL);
        wq_ptr = d_in[3];
        wo_ptr = d_in[4];
    }
    fused_decode_kernel<<<NCTA, NTHREADS, SM_TOTAL, cudaStreamPerThread>>>(tm_wq, tm_wo, x, kc, vc, w1, b1, w2, b2,
                                                                          (__nv_bfloat16*)d_out);
}
```

```cpp
#include <cuda_runtime.h>
#include <cuda.h>
#include <cuda_bf16.h>
#include <stdint.h>

namespace {

constexpr int D_MODEL = 640;
constexpr int NH = 32;
constexpr int SK = 32768;
constexpr int DH = 128;
constexpr int FF = 1728;

constexpr int SPLITS = 4;
constexpr int NCTA = NH * SPLITS;
constexpr int TILE_KEYS = 128;
constexpr int STAGE_BYTES = TILE_KEYS * DH * 2;
constexpr int NTILES = SK / SPLITS / TILE_KEYS;
constexpr int NITEMS = 2 * NTILES;
constexpr int NSTAGE = 6;

constexpr int FILL_WINDOW = 4;

constexpr int QROWS = D_MODEL / SPLITS;
constexpr int WO_ROWS = DH / SPLITS;
constexpr int WO_ROW_BYTES = D_MODEL * 2;
constexpr int WO_BLOCKS = D_MODEL / 64;
constexpr int FCOLS = 8;
constexpr int NFIN = D_MODEL / FCOLS;

constexpr int NCW = 8;
constexpr int NTHREADS = 32 * (NCW + 2);

constexpr int W_STAGE = NSTAGE - 1;
constexpr int SM_W = W_STAGE * STAGE_BYTES;
constexpr int W_BYTES = WO_ROWS * WO_ROW_BYTES;
constexpr int SM_RED = SM_W + W_BYTES;
constexpr int SM_ML = SM_RED + NCW * DH * 4;
constexpr int SM_QS = SM_ML + NCW * 8;
constexpr int SM_OB = SM_QS + DH * 2;
constexpr int SM_FIN = SM_OB + WO_ROWS * 2;
constexpr int SM_MLP = SM_FIN + NCW * FCOLS * 4;
constexpr int SM_OWN = SM_MLP + FCOLS * 4;
constexpr int SM_MW = SM_OWN + FCOLS * 4;
constexpr int SM_BAR = SM_MW + 3 * FF * 2;
constexpr int SM_TOTAL = SM_BAR + (2 * NSTAGE + 4) * 8;
static_assert(SM_MW % 16 == 0 && SM_BAR % 8 == 0 && SM_RED % 16 == 0, "alignment");
static_assert(W_BYTES >= STAGE_BYTES && W_BYTES >= QROWS * DH * 2, "weight buffer");
constexpr int LAST_W = ((NITEMS - 1 - W_STAGE) / NSTAGE) * NSTAGE + W_STAGE;
static_assert(LAST_W < NITEMS - 2, "wo must not wait for the last tile");

constexpr float LOG2E = 1.4426950408889634f;
constexpr float SM_SCALE = 0.08838834764831845f;
constexpr float LN_EPS = 1e-5f;
constexpr uint32_t SPIN_LIMIT = 1u << 24;

struct Scratch {
    unsigned long long qx[NH][SPLITS][DH];
    unsigned int ox[NH][SPLITS][DH + 32];
    unsigned int tx[NFIN][NCTA][FCOLS];
    unsigned int epoch;
};
__device__ __align__(128) Scratch g_scr;

__device__ __forceinline__ uint32_t smem_u32(const void* p) { return (uint32_t)__cvta_generic_to_shared(p); }

__device__ __forceinline__ void mbar_init(uint32_t bar, uint32_t cnt) {
    asm volatile("mbarrier.init.shared::cta.b64 [%0], %1;" ::"r"(bar), "r"(cnt) : "memory");
}
__device__ __forceinline__ void mbar_expect_tx(uint32_t bar, uint32_t bytes) {
    asm volatile("mbarrier.arrive.expect_tx.shared::cta.b64 _, [%0], %1;" ::"r"(bar), "r"(bytes) : "memory");
}
__device__ __forceinline__ void mbar_arrive(uint32_t bar) {
    asm volatile("mbarrier.arrive.shared::cta.b64 _, [%0];" ::"r"(bar) : "memory");
}
__device__ __forceinline__ void mbar_wait(uint32_t bar, uint32_t parity) {
    uint32_t done, it = 0;
    do {
        asm volatile(
            "{\n.reg .pred p;\n"
            "mbarrier.try_wait.parity.shared::cta.b64 p, [%1], %2;\n"
            "selp.u32 %0, 1, 0, p;\n}"
            : "=r"(done) : "r"(bar), "r"(parity) : "memory");
        if (++it > SPIN_LIMIT) __trap();
    } while (!done);
}
__device__ __forceinline__ void bulk_load(uint32_t dst, const void* src, uint32_t bytes, uint32_t bar) {
    asm volatile("cp.async.bulk.shared::cluster.global.mbarrier::complete_tx::bytes [%0], [%1], %2, [%3];"
                 ::"r"(dst), "l"(src), "r"(bytes), "r"(bar) : "memory");
}
__device__ __forceinline__ void bulk_load_stream(uint32_t dst, const void* src, uint32_t bytes, uint32_t bar, uint64_t pol) {
    asm volatile("cp.async.bulk.shared::cluster.global.mbarrier::complete_tx::bytes.L2::cache_hint [%0], [%1], %2, [%3], %4;"
                 ::"r"(dst), "l"(src), "r"(bytes), "r"(bar), "l"(pol) : "memory");
}
__device__ __forceinline__ const uint8_t* item_src(int i, const uint8_t* kbase, const uint8_t* vbase) {
    const bool is_k = (i == 0) || ((i & 1) && i != NITEMS - 1);
    const int tile = is_k ? (i + 1) >> 1 : (i == NITEMS - 1 ? NTILES - 1 : (i >> 1) - 1);
    return (is_k ? kbase : vbase) + (size_t)tile * (SPLITS * STAGE_BYTES);
}
__device__ __forceinline__ void ldsm_x4(uint32_t (&r)[4], uint32_t addr) {
    asm volatile("ldmatrix.sync.aligned.m8n8.x4.shared.b16 {%0,%1,%2,%3}, [%4];"
                 : "=r"(r[0]), "=r"(r[1]), "=r"(r[2]), "=r"(r[3]) : "r"(addr) : "memory");
}
__device__ __forceinline__ void ldsm_x4_t(uint32_t (&r)[4], uint32_t addr) {
    asm volatile("ldmatrix.sync.aligned.m8n8.x4.trans.shared.b16 {%0,%1,%2,%3}, [%4];"
                 : "=r"(r[0]), "=r"(r[1]), "=r"(r[2]), "=r"(r[3]) : "r"(addr) : "memory");
}
__device__ __forceinline__ void mma_bf16(float (&d)[4], const uint32_t (&a)[4], uint32_t b0, uint32_t b1) {
    asm volatile("mma.sync.aligned.m16n8k16.row.col.f32.bf16.bf16.f32 {%0,%1,%2,%3}, {%4,%5,%6,%7}, {%8,%9}, {%0,%1,%2,%3};"
                 : "+f"(d[0]), "+f"(d[1]), "+f"(d[2]), "+f"(d[3])
                 : "r"(a[0]), "r"(a[1]), "r"(a[2]), "r"(a[3]), "r"(b0), "r"(b1));
}
__device__ __forceinline__ float ex2(float x) {
    float y;
    asm("ex2.approx.ftz.f32 %0, %1;" : "=f"(y) : "f"(x));
    return y;
}
__device__ __forceinline__ float bf16r(float x) { return __bfloat162float(__float2bfloat16_rn(x)); }
__device__ __forceinline__ float bf_lo(uint32_t u) { return __uint_as_float(u << 16); }
__device__ __forceinline__ float bf_hi(uint32_t u) { return __uint_as_float(u & 0xffff0000u); }
__device__ __forceinline__ uint32_t pack_bf16(float lo, float hi) {
    uint32_t r;
    asm("cvt.rn.bf16x2.f32 %0, %1, %2;" : "=r"(r) : "f"(hi), "f"(lo));
    return r;
}
__device__ __forceinline__ void named_sync(int id, int n) { asm volatile("bar.sync %0, %1;" ::"r"(id), "r"(n) : "memory"); }
__device__ __forceinline__ void named_arrive(int id, int n) { asm volatile("bar.arrive %0, %1;" ::"r"(id), "r"(n) : "memory"); }

__device__ __forceinline__ void ll_store(unsigned long long* p, float v, uint32_t tag) {
    unsigned long long w = ((unsigned long long)tag << 32) | (unsigned long long)__float_as_uint(v);
    asm volatile("st.relaxed.gpu.global.b64 [%0], %1;" ::"l"(p), "l"(w) : "memory");
}
__device__ __forceinline__ unsigned long long ll_load(const unsigned long long* p) {
    unsigned long long w;
    asm volatile("ld.relaxed.gpu.global.b64 %0, [%1];" : "=l"(w) : "l"(p) : "memory");
    return w;
}
__device__ __forceinline__ bool ll_ok(unsigned long long w, uint32_t tag) { return (uint32_t)(w >> 32) == tag; }
__device__ __forceinline__ float ll_val(unsigned long long w) { return __uint_as_float((uint32_t)w); }

__device__ __forceinline__ void px_store(unsigned int* p, float v, uint32_t par) {
    asm volatile("st.relaxed.gpu.global.b32 [%0], %1;" ::"l"(p), "r"((__float_as_uint(v) & ~1u) | par) : "memory");
}
__device__ __forceinline__ uint32_t px_load(const unsigned int* p) {
    uint32_t w;
    asm volatile("ld.relaxed.gpu.global.b32 %0, [%1];" : "=r"(w) : "l"(p) : "memory");
    return w;
}
__device__ __forceinline__ void px_load2(const unsigned int* p, uint32_t& a, uint32_t& b) {
    asm volatile("ld.relaxed.gpu.global.v2.b32 {%0,%1}, [%2];" : "=r"(a), "=r"(b) : "l"(p) : "memory");
}
__device__ __forceinline__ void px_load4(const unsigned int* p, uint32_t (&w)[4]) {
    asm volatile("ld.relaxed.gpu.global.v4.b32 {%0,%1,%2,%3}, [%4];"
                 : "=r"(w[0]), "=r"(w[1]), "=r"(w[2]), "=r"(w[3]) : "l"(p) : "memory");
}
__device__ __forceinline__ float px_val(uint32_t w) { return __uint_as_float(w & ~1u); }
template <int N>
__device__ __forceinline__ bool px_ready(const uint32_t (&w)[N], uint32_t par) {
    uint32_t bad = 0;
#pragma unroll
    for (int i = 0; i < N; i++) bad |= w[i] ^ par;
    return !(bad & 1u);
}

__device__ __forceinline__ float warp_sum(float v) {
#pragma unroll
    for (int o = 16; o > 0; o >>= 1) v += __shfl_xor_sync(0xffffffffu, v, o);
    return v;
}
__device__ __forceinline__ float warp_max(float v) {
#pragma unroll
    for (int o = 16; o > 0; o >>= 1) v = fmaxf(v, __shfl_xor_sync(0xffffffffu, v, o));
    return v;
}
__device__ __forceinline__ uint2 ldg_u64(const void* p) {
    uint2 v;
    asm volatile("ld.global.nc.v2.u32 {%0,%1}, [%2];" : "=r"(v.x), "=r"(v.y) : "l"(p));
    return v;
}
__device__ __forceinline__ uint32_t ldg_u16(const void* p) {
    uint16_t v;
    asm volatile("ld.global.nc.u16 %0, [%1];" : "=h"(v) : "l"(p));
    return v;
}
__device__ __forceinline__ void unpack_x20(const uint2 (&u)[5], float (&v)[20]) {
#pragma unroll
    for (int i = 0; i < 5; i++) {
        v[4 * i + 0] = bf_lo(u[i].x); v[4 * i + 1] = bf_hi(u[i].x);
        v[4 * i + 2] = bf_lo(u[i].y); v[4 * i + 3] = bf_hi(u[i].y);
    }
}

__device__ __forceinline__ void ln_stats(const float (&v)[20], float& mean_b, float& den_b) {
    float s = 0.f;
#pragma unroll
    for (int i = 0; i < 20; i++) s += v[i];
    const float mean = warp_sum(s) * (1.0f / D_MODEL);
    float q = 0.f;
#pragma unroll
    for (int i = 0; i < 20; i++) { const float d = v[i] - mean; q = fmaf(d, d, q); }
    const float var = warp_sum(q) * (1.0f / D_MODEL);
    mean_b = bf16r(mean);
    den_b = bf16r(sqrtf(bf16r(bf16r(var) + LN_EPS)));
}
__device__ __forceinline__ float ln_apply(float x, float mean_b, float den_b) {
    return bf16r(__fdiv_rn(bf16r(x - mean_b), den_b));
}

__global__ void __launch_bounds__(NTHREADS, 1)
fused_decode_kernel(const __grid_constant__ CUtensorMap tm_wq, const __grid_constant__ CUtensorMap tm_wo,
                    const __nv_bfloat16* __restrict__ x, const __nv_bfloat16* __restrict__ kc,
                    const __nv_bfloat16* __restrict__ vc,
                    const __nv_bfloat16* __restrict__ w1, const __nv_bfloat16* __restrict__ b1,
                    const __nv_bfloat16* __restrict__ w2, const __nv_bfloat16* __restrict__ b2,
                    __nv_bfloat16* __restrict__ out)
{
    extern __shared__ __align__(1024) uint8_t smem[];
    const uint32_t sbase = smem_u32(smem);
    const int tid = threadIdx.x, warp = tid >> 5, lane = tid & 31;
    const int cta = blockIdx.x, head = cta / SPLITS, split = cta % SPLITS;
    const uint32_t bar_full = sbase + SM_BAR, bar_empty = bar_full + NSTAGE * 8, bar_w = bar_empty + NSTAGE * 8,
                   bar_m = bar_w + 8, bar_q = bar_m + 8, bar_qd = bar_q + 8;

    const size_t kv_off = ((size_t)head * SK + (size_t)split * TILE_KEYS) * (DH * 2);
    const uint8_t* kbase = reinterpret_cast<const uint8_t*>(kc) + kv_off;
    const uint8_t* vbase = reinterpret_cast<const uint8_t*>(vc) + kv_off;
    uint64_t pol = 0;

    uint2 xraw[5];
    uint32_t xrow[10];
    uint32_t epoch = 0, xfin = 0;
    if (warp == 0) {
        if (lane == 0) {
            asm volatile("prefetch.tensormap [%0];" ::"l"(&tm_wq) : "memory");
            mbar_init(bar_q, 1);
            asm volatile("fence.proxy.async.shared::cta;" ::: "memory");
            mbar_expect_tx(bar_q, QROWS * DH * 2);
            asm volatile("cp.async.bulk.tensor.2d.shared::cluster.global.mbarrier::complete_tx::bytes [%0], [%1, {%3, %4}], [%2];"
                         ::"r"(sbase + SM_W), "l"(&tm_wq), "r"(bar_q), "r"(head * DH), "r"(split * QROWS) : "memory");
            for (int s = 0; s < NSTAGE; s++) {
                mbar_init(bar_full + s * 8, 1);
                mbar_init(bar_empty + s * 8, NCW);
            }
            mbar_init(bar_w, 1);
            mbar_init(bar_m, 1);
            mbar_init(bar_qd, NCW);
            asm volatile("fence.proxy.async.shared::cta;" ::: "memory");
            asm volatile("createpolicy.fractional.L2::evict_first.b64 %0, 1.0;" : "=l"(pol));
            for (int i = 0; i < FILL_WINDOW; i++) {
                mbar_expect_tx(bar_full + i * 8, STAGE_BYTES);
                bulk_load_stream(sbase + i * STAGE_BYTES, item_src(i, kbase, vbase), STAGE_BYTES, bar_full + i * 8, pol);
            }
        }
        __syncwarp();
        asm volatile("ld.volatile.global.u32 %0, [%1];" : "=r"(epoch) : "l"(&g_scr.epoch) : "memory");
    } else {
        if (warp <= NCW) {
            const int ct = tid - 32;
            asm volatile("ld.volatile.global.u32 %0, [%1];" : "=r"(epoch) : "l"(&g_scr.epoch) : "memory");
#pragma unroll
            for (int i = 0; i < 10; i++) xrow[i] = ldg_u16(x + split * QROWS + (ct >> 4) + 16 * i);
            xfin = ldg_u16(x + (cta < NFIN ? cta * FCOLS : 0) + (ct & (FCOLS - 1)));
        }
#pragma unroll
        for (int i = 0; i < 5; i++) xraw[i] = ldg_u64(reinterpret_cast<const uint2*>(x) + lane + 32 * i);
        if (warp <= NCW) {
            const int ct = tid - 32;
            if (ct < DH) ll_store(&g_scr.qx[head][split][ct], 0.f, 0u);
        }
    }
    __syncthreads();

    if (warp == 0) {
        if (lane == 0) {
            for (int i = FILL_WINDOW; i < NSTAGE; i++) {
                mbar_wait(bar_full + (i - FILL_WINDOW) * 8, 0);
                if (i == W_STAGE) mbar_wait(bar_qd, 0);
                mbar_expect_tx(bar_full + i * 8, STAGE_BYTES);
                bulk_load_stream(sbase + i * STAGE_BYTES, item_src(i, kbase, vbase), STAGE_BYTES, bar_full + i * 8, pol);
            }
            if (cta < NFIN) {
                mbar_expect_tx(bar_m, 3 * FF * 2);
                bulk_load(sbase + SM_MW, w1, FF * 2, bar_m);
                bulk_load(sbase + SM_MW + FF * 2, b1, FF * 2, bar_m);
                bulk_load(sbase + SM_MW + 2 * FF * 2, w2, FF * 2, bar_m);
            }
            asm volatile("prefetch.tensormap [%0];" ::"l"(&tm_wo) : "memory");
            int slot = 0;
            uint32_t ph = 0;
            for (int i = NSTAGE; i < NITEMS; i++) {
                mbar_wait(bar_empty + slot * 8, ph);
                mbar_expect_tx(bar_full + slot * 8, STAGE_BYTES);
                bulk_load_stream(sbase + slot * STAGE_BYTES, item_src(i, kbase, vbase), STAGE_BYTES, bar_full + slot * 8, pol);
                if (++slot == NSTAGE) { slot = 0; ph ^= 1; }
            }
            mbar_wait(bar_empty + W_STAGE * 8, (LAST_W / NSTAGE) & 1);
            mbar_expect_tx(bar_w, W_BYTES);
            asm volatile("cp.async.bulk.tensor.3d.shared::cluster.global.mbarrier::complete_tx::bytes [%0], [%1, {%3, %4, %3}], [%2];"
                         ::"r"(sbase + SM_W), "l"(&tm_wo), "r"(bar_w), "r"(0), "r"(head * DH + split * WO_ROWS) : "memory");
        }
        __syncwarp();

        {
            const uint32_t par = (epoch + 1u) & 1u;
            uint32_t ml[2 * SPLITS];
            uint32_t it = 0;
            do {
#pragma unroll
                for (int i = 0; i < SPLITS; i++) px_load2(&g_scr.ox[head][i][DH], ml[2 * i], ml[2 * i + 1]);
                if (++it > SPIN_LIMIT) __trap();
            } while (!px_ready(ml, par));
            const float M = fmaxf(fmaxf(px_val(ml[0]), px_val(ml[2])), fmaxf(px_val(ml[4]), px_val(ml[6])));
            float e[SPLITS], L = 0.f;
#pragma unroll
            for (int i = 0; i < SPLITS; i++) {
                e[i] = ex2((px_val(ml[2 * i]) - M) * LOG2E);
                L = fmaf(e[i], px_val(ml[2 * i + 1]), L);
            }
#pragma unroll
            for (int i = 0; i < SPLITS; i++) e[i] = __fdiv_rn(e[i], L);
            uint32_t w4[SPLITS];
            do {
#pragma unroll
                for (int i = 0; i < SPLITS; i++) w4[i] = px_load(&g_scr.ox[head][i][split * WO_ROWS + lane]);
                if (++it > SPIN_LIMIT) __trap();
            } while (!px_ready(w4, par));
            const float o = fmaf(e[0], px_val(w4[0]), e[1] * px_val(w4[1])) + fmaf(e[2], px_val(w4[2]), e[3] * px_val(w4[3]));
            reinterpret_cast<__nv_bfloat16*>(smem + SM_OB)[lane] = __float2bfloat16_rn(o);
            __syncwarp();
            named_arrive(3, NCW * 32 + 32);
        }
    } else if (warp <= NCW) {
        const int cw = warp - 1, ct = tid - 32;
        const int g = lane >> 2, t = lane & 3;
        float* red = reinterpret_cast<float*>(smem + SM_RED);
        const uint32_t tag = epoch + 1u, par = tag & 1u;
        if (ct < DH + 32) px_store(&g_scr.ox[head][split][ct], 0.f, par ^ 1u);
#pragma unroll
        for (int k = 0; k < 3; k++) {
            const int idx = ct + 256 * k;
            if (idx < D_MODEL) px_store(&g_scr.tx[idx / FCOLS][cta][idx % FCOLS], 0.f, par ^ 1u);
        }

        {
            float xv[20];
            unpack_x20(xraw, xv);
            float mean_b, den_b;
            ln_stats(xv, mean_b, den_b);
            float a[8];
#pragma unroll
            for (int j = 0; j < 8; j++) a[j] = 0.f;
            float xn[10];
#pragma unroll
            for (int i = 0; i < 10; i++) xn[i] = ln_apply(bf_lo(xrow[i]), mean_b, den_b);
            mbar_wait(bar_q, 0);
            const uint4* wsm = reinterpret_cast<const uint4*>(smem + SM_W) + ct;
#pragma unroll
            for (int i = 0; i < 10; i++) {
                const uint4 w = wsm[i * 256];
                a[0] = fmaf(xn[i], bf_lo(w.x), a[0]); a[1] = fmaf(xn[i], bf_hi(w.x), a[1]);
                a[2] = fmaf(xn[i], bf_lo(w.y), a[2]); a[3] = fmaf(xn[i], bf_hi(w.y), a[3]);
                a[4] = fmaf(xn[i], bf_lo(w.z), a[4]); a[5] = fmaf(xn[i], bf_hi(w.z), a[5]);
                a[6] = fmaf(xn[i], bf_lo(w.w), a[6]); a[7] = fmaf(xn[i], bf_hi(w.w), a[7]);
            }
            __syncwarp();
            if (lane == 0) mbar_arrive(bar_qd);
#pragma unroll
            for (int j = 0; j < 8; j++) a[j] += __shfl_xor_sync(0xffffffffu, a[j], 16);
            if (lane < 16) {
                float4* dst = reinterpret_cast<float4*>(red + cw * DH + lane * 8);
                dst[0] = make_float4(a[0], a[1], a[2], a[3]);
                dst[1] = make_float4(a[4], a[5], a[6], a[7]);
            }
            named_sync(1, NCW * 32);
            if (ct < DH) {
                float s = 0.f;
#pragma unroll
                for (int w = 0; w < NCW; w++) s += red[w * DH + ct];
                ll_store(&g_scr.qx[head][split][ct], s, tag);
                unsigned long long w4[SPLITS];
                uint32_t it = 0;
                bool ok;
                do {
#pragma unroll
                    for (int i = 0; i < SPLITS; i++) w4[i] = ll_load(&g_scr.qx[head][i][ct]);
                    ok = true;
#pragma unroll
                    for (int i = 0; i < SPLITS; i++) ok = ok && ll_ok(w4[i], tag);
                    if (++it > SPIN_LIMIT) __trap();
                } while (!ok);
                const float q = (ll_val(w4[0]) + ll_val(w4[1])) + (ll_val(w4[2]) + ll_val(w4[3]));
                reinterpret_cast<__nv_bfloat16*>(smem + SM_QS)[ct] = __float2bfloat16_rn(q);
            }
            named_sync(1, NCW * 32);
        }

        uint32_t qf[8][2];
#pragma unroll
        for (int s = 0; s < 8; s++) {
            const uint32_t* qs = reinterpret_cast<const uint32_t*>(smem + SM_QS);
            qf[s][0] = qs[4 * (s ^ g) + t];
            qf[s][1] = qs[32 + 4 * (s ^ g) + t];
        }

        float acc[8][4];
#pragma unroll
        for (int c = 0; c < 8; c++) { acc[c][0] = acc[c][1] = acc[c][2] = acc[c][3] = 0.f; }
        float m_run = -INFINITY, l_run = 0.f;
        const bool valid = (t == (g >> 1));
        const bool odd = g & 1;
        const uint32_t sel0 = odd ? 0x1044u : 0x4410u;
        const uint32_t sel1 = odd ? 0x3244u : 0x4432u;
        const int mi = lane >> 3, rho = lane & 7;
        const uint32_t k_off = (uint32_t)(cw * 16 + rho + 8 * (mi & 1)) * 256u + (uint32_t)(mi >> 1) * 128u + (uint32_t)rho * 16u;
        const uint32_t v_off = (uint32_t)(cw * 16 + rho + 8 * (mi >> 1)) * 256u + (uint32_t)(mi & 1) * 128u + (uint32_t)rho * 16u;

        int slot = 0;
        uint32_t ph = 0;
        auto qk_tile = [&](float& sa, float& sb) {
            const uint32_t ka = sbase + slot * STAGE_BYTES + k_off;
            mbar_wait(bar_full + slot * 8, ph);
            float s0[4] = {0.f, 0.f, 0.f, 0.f}, s1[4] = {0.f, 0.f, 0.f, 0.f};
#pragma unroll
            for (int s = 0; s < 8; s += 2) {
                uint32_t r[4], u[4];
                ldsm_x4(r, ka ^ (uint32_t)(s << 4));
                ldsm_x4(u, ka ^ (uint32_t)((s + 1) << 4));
                mma_bf16(s0, r, qf[s][0], qf[s][1]);
                mma_bf16(s1, u, qf[s + 1][0], qf[s + 1][1]);
            }
            __syncwarp();
            if (lane == 0) mbar_arrive(bar_empty + slot * 8);
            if (++slot == NSTAGE) { slot = 0; ph ^= 1; }
            const float ra = odd ? (s0[1] + s1[1]) : (s0[0] + s1[0]);
            const float rb = odd ? (s0[3] + s1[3]) : (s0[2] + s1[2]);
            sa = valid ? bf16r(bf16r(ra) * SM_SCALE) : -INFINITY;
            sb = valid ? bf16r(bf16r(rb) * SM_SCALE) : -INFINITY;
        };
        auto raise_max = [&](float m_new) {
            const float sc = ex2((m_run - m_new) * LOG2E);
#pragma unroll
            for (int c = 0; c < 8; c++) { acc[c][0] *= sc; acc[c][1] *= sc; acc[c][2] *= sc; acc[c][3] *= sc; }
            l_run *= sc;
            m_run = m_new;
        };
        auto probs = [&](float sa, float sb, uint32_t& b0, uint32_t& b1) {
            const float pa = ex2((sa - m_run) * LOG2E);
            const float pb = ex2((sb - m_run) * LOG2E);
            l_run += pa + pb;
            const uint32_t pk = pack_bf16(pa, pb);
            b0 = __byte_perm(pk, 0u, sel0);
            b1 = __byte_perm(pk, 0u, sel1);
        };
        auto pv_tile = [&](uint32_t b0, uint32_t b1) {
            const uint32_t va = sbase + slot * STAGE_BYTES + v_off;
            mbar_wait(bar_full + slot * 8, ph);
#pragma unroll
            for (int c = 0; c < 8; c++) {
                uint32_t r[4];
                ldsm_x4_t(r, va ^ (uint32_t)(c << 4));
                mma_bf16(acc[c], r, b0, b1);
            }
            __syncwarp();
            if (lane == 0) mbar_arrive(bar_empty + slot * 8);
            if (++slot == NSTAGE) { slot = 0; ph ^= 1; }
        };

        float ca, cb;
        qk_tile(ca, cb);
        m_run = warp_max(fmaxf(ca, cb));
#pragma unroll 1
        for (int tile = 0; tile < NTILES - 2; tile++) {
            float na, nb;
            qk_tile(na, nb);
            const float smax = fmaxf(na, nb);
            if (__any_sync(0xffffffffu, smax > m_run)) raise_max(warp_max(smax));
            uint32_t b0, b1;
            probs(ca, cb, b0, b1);
            pv_tile(b0, b1);
            ca = na; cb = nb;
        }
        {
            float na, nb;
            qk_tile(na, nb);
            float* mw = reinterpret_cast<float*>(smem + SM_ML);
            const float m_new = fmaxf(m_run, warp_max(fmaxf(na, nb)));
            if (lane == 0) mw[cw] = m_new;
            named_sync(1, NCW * 32);
            const float4 ma = *reinterpret_cast<const float4*>(mw), mb = *reinterpret_cast<const float4*>(mw + 4);
            raise_max(fmaxf(fmaxf(fmaxf(ma.x, ma.y), fmaxf(ma.z, ma.w)), fmaxf(fmaxf(mb.x, mb.y), fmaxf(mb.z, mb.w))));
            uint32_t b0, b1, c0, c1;
            probs(ca, cb, b0, b1);
            probs(na, nb, c0, c1);
            const float lw = warp_sum(l_run);
            if (lane == 0) mw[NCW + cw] = lw;
            named_sync(1, NCW * 32);
            if (ct == 0) {
                const float4 la = *reinterpret_cast<const float4*>(mw + NCW), lb = *reinterpret_cast<const float4*>(mw + NCW + 4);
                px_store(&g_scr.ox[head][split][DH], m_run, par);
                px_store(&g_scr.ox[head][split][DH + 1], ((la.x + la.y) + (la.z + la.w)) + ((lb.x + lb.y) + (lb.z + lb.w)), par);
            }
            pv_tile(b0, b1);
            pv_tile(c0, c1);
        }

        {
            float u[2][8];
#pragma unroll
            for (int c = 0; c < 8; c++) {
                u[0][c] = acc[c][0] + acc[c ^ 1][1];
                u[1][c] = acc[c][2] + acc[c ^ 1][3];
            }
#pragma unroll
            for (int hf = 0; hf < 2; hf++) {
#pragma unroll
                for (int c = 0; c < 8; c++)
                    if (!(c & 2)) u[hf][c] += __shfl_xor_sync(0xffffffffu, u[hf][c ^ 2], 1);
                u[hf][0] += __shfl_xor_sync(0xffffffffu, u[hf][4], 2);
                u[hf][1] += __shfl_xor_sync(0xffffffffu, u[hf][5], 2);
                red[cw * DH + 64 * hf + 16 * t + g] = u[hf][0];
                red[cw * DH + 64 * hf + 16 * t + 8 + g] = u[hf][1];
            }
        }
        named_sync(1, NCW * 32);

        if (ct < DH) {
            const float o = ((red[ct] + red[DH + ct]) + (red[2 * DH + ct] + red[3 * DH + ct])) +
                            ((red[4 * DH + ct] + red[5 * DH + ct]) + (red[6 * DH + ct] + red[7 * DH + ct]));
            px_store(&g_scr.ox[head][split][ct], o, par);
        }

        unsigned int* txp = &g_scr.tx[cw * 10 + t][cta][g];
        uint32_t wa[5];
#pragma unroll
        for (int i = 0; i < 5; i++) {
            const int col = cw * 80 + 16 * i + 8 * (mi & 1), row = rho + 8 * (mi >> 1);
            wa[i] = sbase + SM_W + (uint32_t)(col >> 6) * (WO_ROWS * 128) + (uint32_t)row * 128u + (uint32_t)((((col >> 3) & 7) ^ rho) << 4);
        }
        mbar_wait(bar_w, 0);
        uint32_t wf[5][2][4];
#pragma unroll
        for (int i = 0; i < 5; i++) {
            ldsm_x4_t(wf[i][0], wa[i]);
            ldsm_x4_t(wf[i][1], wa[i] + 16 * 128);
        }
        const unsigned int* src = &g_scr.tx[cta < NFIN ? cta : 0][ct >> 1][(ct & 1) * 4];
        const bool own_src = (ct >> 1) == cta;
        uint32_t w[4] = {par ^ 1u, par ^ 1u, par ^ 1u, par ^ 1u};
        if (cta < NFIN && !own_src) px_load4(src, w);
        named_sync(3, NCW * 32 + 32);

        {
            const uint32_t* ob = reinterpret_cast<const uint32_t*>(smem + SM_OB);
            const uint32_t b00 = ob[t], b01 = ob[4 + t], b10 = ob[8 + t], b11 = ob[12 + t];
            float d[5][4];
#pragma unroll
            for (int i = 0; i < 5; i++) {
                d[i][0] = d[i][1] = d[i][2] = d[i][3] = 0.f;
                mma_bf16(d[i], wf[i][0], b00, b01);
                mma_bf16(d[i], wf[i][1], b10, b11);
            }
#pragma unroll
            for (int k = 0; k < 3; k++) {
                const int i0 = 2 * k, i1 = (2 * k + 1 < 5) ? 2 * k + 1 : 2 * k;
                const float v0 = (t & 1) ? d[i0][2] : d[i0][0];
                const float v1 = (t & 1) ? d[i1][2] : d[i1][0];
                const float v = (t >> 1) ? v1 : v0;
                if (k < 2 || t < 2) {
                    if (cw * 10 + 4 * k + t == cta) reinterpret_cast<float*>(smem + SM_OWN)[g] = v;
                    else px_store(txp + (size_t)(4 * k) * NCTA * FCOLS, v, par);
                }
            }
        }

        if (cta < NFIN) {
            if (!own_src) {
                uint32_t it = 0;
                while (!px_ready(w, par)) {
                    px_load4(src, w);
                    if (++it > SPIN_LIMIT) __trap();
                }
            }
            __syncwarp();
            const float v0 = own_src ? 0.f : px_val(w[0]), v1 = own_src ? 0.f : px_val(w[1]);
            const float v2 = own_src ? 0.f : px_val(w[2]), v3 = own_src ? 0.f : px_val(w[3]);
            const bool q1 = lane & 2, q2 = lane & 4;
            float k0 = q1 ? v2 : v0, k1 = q1 ? v3 : v1;
            k0 += __shfl_xor_sync(0xffffffffu, q1 ? v0 : v2, 2);
            k1 += __shfl_xor_sync(0xffffffffu, q1 ? v1 : v3, 2);
            float k = q2 ? k1 : k0;
            k += __shfl_xor_sync(0xffffffffu, q2 ? k0 : k1, 4);
            k += __shfl_xor_sync(0xffffffffu, k, 8);
            k += __shfl_xor_sync(0xffffffffu, k, 16);
            if (lane < 8)
                reinterpret_cast<float*>(smem + SM_FIN)[cw * 8 + 4 * (lane & 1) + (lane & 2) + (lane >> 2)] = k;
            named_sync(2, NCW * 32 + 32);
            if (ct < FCOLS) {
                const float* fin = reinterpret_cast<const float*>(smem + SM_FIN);
                const float a = ((fin[ct] + fin[FCOLS + ct]) + (fin[2 * FCOLS + ct] + fin[3 * FCOLS + ct])) +
                                ((fin[4 * FCOLS + ct] + fin[5 * FCOLS + ct]) + (fin[6 * FCOLS + ct] + fin[7 * FCOLS + ct]));
                const float r = bf16r(bf_lo(xfin) + bf16r(a + reinterpret_cast<const float*>(smem + SM_OWN)[ct]));
                out[cta * FCOLS + ct] = __float2bfloat16_rn(r + reinterpret_cast<const float*>(smem + SM_MLP)[ct]);
                if (cta == 0 && ct == 0) *reinterpret_cast<volatile unsigned int*>(&g_scr.epoch) = tag;
            }
        }
    } else if (cta < NFIN) {
        float xv[20];
        unpack_x20(xraw, xv);
        float mean_b, den_b;
        ln_stats(xv, mean_b, den_b);
#pragma unroll
        for (int i = 0; i < 20; i++) xv[i] = ln_apply(xv[i], mean_b, den_b);
        float mean2, den2;
        ln_stats(xv, mean2, den2);
        const __nv_bfloat16* mw = reinterpret_cast<const __nv_bfloat16*>(smem + SM_MW);
        const float bias2 = __bfloat162float(b2[0]);
        mbar_wait(bar_m, 0);
        float h[FCOLS], y[FCOLS];
#pragma unroll
        for (int j = 0; j < FCOLS; j++) {
            const float xn = ln_apply(__bfloat162float(x[cta * FCOLS + j]), mean_b, den_b);
            h[j] = ln_apply(xn, mean2, den2);
            y[j] = 0.f;
        }
        for (int f = lane; f < FF; f += 32) {
            const float a = __bfloat162float(mw[f]), b = __bfloat162float(mw[FF + f]), c = __bfloat162float(mw[2 * FF + f]);
#pragma unroll
            for (int j = 0; j < FCOLS; j++) {
                const float u = bf16r(bf16r(h[j] * a) + b);
                const float inner = 0.7978845608028654f * (u + 0.044715f * u * u * u);
                const float gl = bf16r(0.5f * u * (1.0f + tanhf(inner)));
                y[j] = fmaf(gl, c, y[j]);
            }
        }
#pragma unroll
        for (int j = 0; j < FCOLS; j++) {
            const float s = warp_sum(y[j]);
            if (lane == j) reinterpret_cast<float*>(smem + SM_MLP)[j] = bf16r(bf16r(s) + bias2);
        }
        __syncwarp();
        named_arrive(2, NCW * 32 + 32);
    }
}

}

extern "C" void kernel_launch(void* const* d_in, const int* in_sizes, int n_in, void* d_out, int out_size) {
    (void)in_sizes; (void)n_in; (void)out_size;
    const __nv_bfloat16* x = (const __nv_bfloat16*)d_in[0];
    const __nv_bfloat16* kc = (const __nv_bfloat16*)d_in[1];
    const __nv_bfloat16* vc = (const __nv_bfloat16*)d_in[2];
    const __nv_bfloat16* w1 = (const __nv_bfloat16*)d_in[6];
    const __nv_bfloat16* b1 = (const __nv_bfloat16*)d_in[7];
    const __nv_bfloat16* w2 = (const __nv_bfloat16*)d_in[8];
    const __nv_bfloat16* b2 = (const __nv_bfloat16*)d_in[9];

    static CUtensorMap tm_wq, tm_wo;
    static void *wq_ptr = nullptr, *wo_ptr = nullptr;
    if (wq_ptr != d_in[3] || wo_ptr != d_in[4]) {
        typedef CUresult (*encode_fn)(CUtensorMap*, CUtensorMapDataType, cuuint32_t, void*, const cuuint64_t*,
                                      const cuuint64_t*, const cuuint32_t*, const cuuint32_t*, CUtensorMapInterleave,
                                      CUtensorMapSwizzle, CUtensorMapL2promotion, CUtensorMapFloatOOBfill);
        void* fn = nullptr;
        cudaDriverEntryPointQueryResult qr;
        cudaGetDriverEntryPoint("cuTensorMapEncodeTiled", &fn, cudaEnableDefault, &qr);
        const cuuint64_t gdim[2] = {(cuuint64_t)(NH * DH), (cuuint64_t)D_MODEL};
        const cuuint64_t gstride[1] = {(cuuint64_t)(NH * DH * 2)};
        const cuuint32_t box[2] = {(cuuint32_t)DH, (cuuint32_t)QROWS};
        const cuuint32_t estride[2] = {1, 1};
        ((encode_fn)fn)(&tm_wq, CU_TENSOR_MAP_DATA_TYPE_BFLOAT16, 2, d_in[3], gdim, gstride, box, estride,
                        CU_TENSOR_MAP_INTERLEAVE_NONE, CU_TENSOR_MAP_SWIZZLE_NONE, CU_TENSOR_MAP_L2_PROMOTION_NONE,
                        CU_TENSOR_MAP_FLOAT_OOB_FILL_NONE);
        const cuuint64_t odim[3] = {64, (cuuint64_t)(NH * DH), (cuuint64_t)WO_BLOCKS};
        const cuuint64_t ostride[2] = {(cuuint64_t)WO_ROW_BYTES, 128};
        const cuuint32_t obox[3] = {64, (cuuint32_t)WO_ROWS, (cuuint32_t)WO_BLOCKS};
        const cuuint32_t oestride[3] = {1, 1, 1};
        ((encode_fn)fn)(&tm_wo, CU_TENSOR_MAP_DATA_TYPE_BFLOAT16, 3, d_in[4], odim, ostride, obox, oestride,
                        CU_TENSOR_MAP_INTERLEAVE_NONE, CU_TENSOR_MAP_SWIZZLE_128B, CU_TENSOR_MAP_L2_PROMOTION_NONE,
                        CU_TENSOR_MAP_FLOAT_OOB_FILL_NONE);
        cudaFuncSetAttribute(fused_decode_kernel, cudaFuncAttributeMaxDynamicSharedMemorySize, SM_TOTAL);
        wq_ptr = d_in[3];
        wo_ptr = d_in[4];
    }
    fused_decode_kernel<<<NCTA, NTHREADS, SM_TOTAL, cudaStreamPerThread>>>(tm_wq, tm_wo, x, kc, vc, w1, b1, w2, b2,
                                                                          (__nv_bfloat16*)d_out);
}
```
